```python
import torch

def _softmax(x, axis=-1):
    return torch.softmax(x, dim=axis)
def _gelu(x):
    return torch.nn.functional.gelu(x, approximate="tanh")
def _silu(x):
    return torch.nn.functional.silu(x)
def _sigmoid(x):
    return torch.sigmoid(x)
def _layernorm(x, axis=-1, eps=1e-5):
    m = x.mean(dim=axis, keepdim=True)
    v = x.var(dim=axis, keepdim=True, unbiased=False)
    return (x - m) / torch.sqrt(v + eps)
def _scatter_add(tgt, idx, src, axis=0):
    return tgt.clone().index_add_(axis, idx, src)
def _segment_sum(src, seg, n):
    out = torch.zeros((n,) + src.shape[1:], dtype=src.dtype)
    return out.index_add_(0, seg, src)
def _pad(x, pw):
    flat = tuple(v for pair in reversed(pw) for v in pair)
    return torch.nn.functional.pad(x, flat)

kernel_name = 'sequential_preLN__sliding_block_cached__dense_activation_silu__decode'

def setup_inputs():

    _w = (lambda a: (lambda t: t.to(torch.bfloat16) if t.is_floating_point() else t)(torch.as_tensor(a)))
    def _A_setup():
        B, Sq, D = 1, 1, 576
        Hq, Hkv, Sk, Dh = 32, 16, 8192, 128
        assert Hq % Hkv == 0, (Hq, Hkv)
        return {
            "x": _w((lambda *s: torch.randn(*s, dtype=torch.bfloat16) * 0.05)(B, Sq, D)),
            "k_cache": _w((lambda *s: torch.randn(*s, dtype=torch.bfloat16) * 3.2)(B, Hkv, Sk, Dh)),
            "v_cache": _w((lambda *s: torch.randn(*s, dtype=torch.bfloat16) * 0.8)(B, Hkv, Sk, Dh)),
            "wq": _w((lambda *s: torch.randn(*s, dtype=torch.bfloat16) * 3.2)(D, Hq * Dh) * (D ** -0.5)),
            "wo": _w((lambda *s: torch.randn(*s, dtype=torch.bfloat16) * 0.8)(Hq * Dh, D) * ((Hq * Dh) ** -0.5)),
        }
    _A_in = _A_setup()

    def _B_setup():
        B, S, D, F = 1, 1, 576, 4608
        return {
            "x": _w((lambda *s: torch.randn(*s, dtype=torch.bfloat16) * 0.05)(B, S, D)),
            "w1": _w((lambda *s: torch.randn(*s, dtype=torch.bfloat16) * 3.2)(D, F) * (D ** -0.5)),
            "w2": _w((lambda *s: torch.randn(*s, dtype=torch.bfloat16) * 0.4)(F, D) * (F ** -0.5)),
        }
    _B_in = _B_setup()

    return {
        "A_x": _A_in["x"],
        "A_k_cache": _A_in["k_cache"],
        "A_v_cache": _A_in["v_cache"],
        "A_wq": _A_in["wq"],
        "A_wo": _A_in["wo"],
        "B_x": _B_in["x"],
        "B_w1": _B_in["w1"],
        "B_w2": _B_in["w2"],
    }

def reference(A_x, A_k_cache, A_v_cache, A_wq, A_wo, B_x, B_w1, B_w2):
    def _A_ref(x, k_cache, v_cache, wq, wo):
        B, Sq, D = x.shape
        Hq, Dh = 32, 128
        Hkv, Sk = k_cache.shape[1], k_cache.shape[2]
        W = min(4096, max(256, Sk // 4))
        rep = Hq // Hkv
        q = (lambda x, *d: x.permute(*d))((x @ wq).reshape(B, Sq, Hq, Dh), 0, 2, 1, 3)
        k = (lambda x, n, axis: torch.repeat_interleave(x, n, dim=axis))(k_cache[:, :, Sk - W:, :], rep, axis=1)
        v = (lambda x, n, axis: torch.repeat_interleave(x, n, dim=axis))(v_cache[:, :, Sk - W:, :], rep, axis=1)
        scores = torch.einsum("bhqd,bhkd->bhqk", q, k) * (Dh ** -0.5)
        p = _softmax(scores, axis=-1)
        o = torch.einsum("bhqk,bhkd->bhqd", p, v)
        return (lambda x, *d: x.permute(*d))(o, 0, 2, 1, 3).reshape(B, Sq, Hq * Dh) @ wo

    def _B_ref(x, w1, w2):
        h = torch.einsum("bsd,df->bsf", x, w1)
        h = _silu(h)
        out = torch.einsum("bsf,fd->bsd", h, w2)
        return out

    x = A_x
    h = x + _A_ref(_layernorm(x, axis=-1), A_k_cache, A_v_cache, A_wq, A_wo)
    h2 = h + _B_ref(_layernorm(h, axis=-1), B_w1, B_w2)
    return h2
```

```cpp
#include <cuda_runtime.h>
#include <cuda_bf16.h>
#include <stdint.h>

namespace {

constexpr int DM = 576, SK = 8192, WIN = 2048, FF = 4608;
constexpr int CS = 6, NCL = 16, NCTA = CS * NCL;
constexpr int NMMA = 18;
constexpr int EW0 = 18;
constexpr int PW0 = 21, NPROD = 4;
constexpr int NTHREADS = (PW0 + NPROD) * 32;

constexpr int PACE_T0 = 925, T_K = 2750, T_V = 2710, T_O = 1600, TAU_1 = 300, TAU_2A = 300, TAU_2B = 250, WIN_CAP = 13;
#define SETS3 1
#define GAP3 300
#define SETS5 1
#define GAP5 110
#define RED3 0
#define RED5 0
#define X3ATOM 1
#define POLL32_IF(v, p) asm volatile("{.reg .pred q; setp.eq.u32 q, %0, 0xFFFFFFFF; @q atom.relaxed.gpu.global.or.b32 %0, [%1], 0;}" : "+r"(v) : "l"(p) : "memory")
#define X5W3 0
#define USE_EVICT_FIRST 1

constexpr int WQ_PITCH = 528, KV_GRP = 1040, KV_STAGE = 8 * KV_GRP, WR_PITCH = 1168, WR_STAGE = 8 * WR_PITCH;
constexpr int W1_PITCH = 592, W1_STAGE = 16 * W1_PITCH, WQ_STAGE = 16 * WQ_PITCH;
constexpr int WQ_OFF = 0;
constexpr int K_OFF = 96 * WQ_PITCH;
constexpr int V_OFF = K_OFF + 11 * KV_STAGE;
constexpr int RING_END = V_OFF + 8 * KV_STAGE;
constexpr int WO_OFF = 3 * KV_STAGE;
constexpr int W1_OFF = WO_OFF + 6 * WR_STAGE;
constexpr int W2_OFF = W1_OFF + 6 * W1_STAGE;
static_assert(W2_OFF + 6 * WR_STAGE <= V_OFF + 7 * KV_STAGE, "w2 must only overlap V stages 0..6");
constexpr int X1R = RING_END;
constexpr int X2R = X1R + 6144;
constexpr int X2S = X2R + 1152;
constexpr int X3R = X2S + 96;
constexpr int X4R = X3R + 2304;
constexpr int X4S = X4R + 2304;
constexpr int Q_S = X4S + 288;
constexpr int XN_S = Q_S + 640;
constexpr int X_S = XN_S + 192;
constexpr int P_S = X_S + 384;
constexpr int WMAX = P_S + 1408;
constexpr int WSUM = WMAX + 160;
constexpr int O_S = WSUM + 160;
constexpr int H_S = O_S + 96;
constexpr int HF_S = H_S + 192;
constexpr int H1_S = HF_S + 384;
constexpr int BARS = H1_S + 96;
constexpr int B_WQ = 0, B_K = 12, B_V = 23, B_WO = 34, B_W1 = 40, B_W2 = 46;
constexpr int B_WQDONE = 52, B_KDONE = 53, B_VDONE = 54;
constexpr int B_X1 = 55, B_X2 = 56, B_X3 = 57, B_X4 = 58, B_X4S = 59;
constexpr int B_Q = 60, B_O = 61, B_H = 62, B_H1 = 63, B_INIT = 64;
constexpr int NBAR = 65;
constexpr int SMEM_BYTES = BARS + NBAR * 8;
static_assert(BARS % 8 == 0 && X2S % 16 == 0 && Q_S % 16 == 0 && X4R % 16 == 0 && X1R % 16 == 0, "align");
static_assert(SMEM_BYTES <= 232448, "smem");

constexpr uint32_t SENT = 0xFFFFFFFFu;

constexpr int NOWN = 72;
__device__ uint4 g_slot3[CS * NCL * 24];
__device__ uint4 g_slot5[NOWN * NCTA * 2];
__device__ unsigned g_arrive;

#define TL(i) do { } while (0)

__device__ __forceinline__ void mbar_init(uint32_t b, uint32_t c) { asm volatile("mbarrier.init.shared::cta.b64 [%0], %1;" ::"r"(b), "r"(c) : "memory"); }
__device__ __forceinline__ void mbar_expect(uint32_t b, uint32_t bytes) { asm volatile("mbarrier.arrive.expect_tx.shared::cta.b64 _, [%0], %1;" ::"r"(b), "r"(bytes) : "memory"); }
__device__ __forceinline__ void mbar_arrive(uint32_t b) { asm volatile("mbarrier.arrive.shared::cta.b64 _, [%0];" ::"r"(b) : "memory"); }
__device__ __forceinline__ void mbar_wait(uint32_t b) {
    asm volatile("{\n.reg .pred p;\n.reg .u32 n;\nmov.u32 n, 0;\n"
                 "W_LOOP:\nmbarrier.try_wait.parity.shared::cta.b64 p, [%0], 0;\n@p bra W_DONE;\n"
                 "add.u32 n, n, 1;\nsetp.lt.u32 p, n, 0x400000;\n@p bra W_LOOP;\ntrap;\nW_DONE:\n}" ::"r"(b) : "memory");
}
__device__ __forceinline__ bool elect() { uint32_t p; asm volatile("{.reg .pred P; elect.sync _|P, 0xffffffff; selp.u32 %0,1,0,P;}" : "=r"(p)); return p; }
__device__ __forceinline__ float ex2(float x) { float y; asm("ex2.approx.ftz.f32 %0, %1;" : "=f"(y) : "f"(x)); return y; }
__device__ __forceinline__ float sqrt_fast(float x) { float y; asm("sqrt.approx.f32 %0, %1;" : "=f"(y) : "f"(x)); return y; }
__device__ __forceinline__ void bulk_g2s(uint32_t dst, const void* src, uint32_t bytes, uint32_t bar, uint64_t pol) {
    asm volatile("cp.async.bulk.shared::cluster.global.mbarrier::complete_tx::bytes.L2::cache_hint [%0], [%1], %2, [%3], %4;" ::"r"(dst), "l"(src), "r"(bytes), "r"(bar), "l"(pol) : "memory");
}
__device__ __forceinline__ uint32_t mapa(uint32_t a, uint32_t rank) { uint32_t r; asm("mapa.shared::cluster.u32 %0, %1, %2;" : "=r"(r) : "r"(a), "r"(rank)); return r; }
__device__ __forceinline__ void st_async1(uint32_t a, float v, uint32_t bar) { asm volatile("st.async.shared::cluster.mbarrier::complete_tx::bytes.b32 [%0], %1, [%2];" ::"r"(a), "r"(__float_as_uint(v)), "r"(bar) : "memory"); }
__device__ __forceinline__ void st_async2(uint32_t a, float x, float y, uint32_t bar) { asm volatile("st.async.shared::cluster.mbarrier::complete_tx::bytes.v2.b32 [%0], {%1,%2}, [%3];" ::"r"(a), "r"(__float_as_uint(x)), "r"(__float_as_uint(y)), "r"(bar) : "memory"); }
__device__ __forceinline__ void st_async4(uint32_t a, float x, float y, float z, float w, uint32_t bar) { asm volatile("st.async.shared::cluster.mbarrier::complete_tx::bytes.v4.b32 [%0], {%1,%2,%3,%4}, [%5];" ::"r"(a), "r"(__float_as_uint(x)), "r"(__float_as_uint(y)), "r"(__float_as_uint(z)), "r"(__float_as_uint(w)), "r"(bar) : "memory"); }
__device__ __forceinline__ void ldsm4(uint32_t (&r)[4], uint32_t a) { asm volatile("ldmatrix.sync.aligned.m8n8.x4.shared.b16 {%0,%1,%2,%3}, [%4];" : "=r"(r[0]), "=r"(r[1]), "=r"(r[2]), "=r"(r[3]) : "r"(a) : "memory"); }
__device__ __forceinline__ void ldsm4t(uint32_t (&r)[4], uint32_t a) { asm volatile("ldmatrix.sync.aligned.m8n8.x4.trans.shared.b16 {%0,%1,%2,%3}, [%4];" : "=r"(r[0]), "=r"(r[1]), "=r"(r[2]), "=r"(r[3]) : "r"(a) : "memory"); }
__device__ __forceinline__ void mma16(float (&c)[4], const uint32_t (&a)[4], uint32_t b0, uint32_t b1) {
    asm volatile("mma.sync.aligned.m16n8k16.row.col.f32.bf16.bf16.f32 {%0,%1,%2,%3}, {%4,%5,%6,%7}, {%8,%9}, {%0,%1,%2,%3};"
                 : "+f"(c[0]), "+f"(c[1]), "+f"(c[2]), "+f"(c[3]) : "r"(a[0]), "r"(a[1]), "r"(a[2]), "r"(a[3]), "r"(b0), "r"(b1));
}
__device__ __forceinline__ void mma8(float (&c)[4], uint32_t a0, uint32_t a1, uint32_t b0) {
    asm volatile("mma.sync.aligned.m16n8k8.row.col.f32.bf16.bf16.f32 {%0,%1,%2,%3}, {%4,%5}, {%6}, {%0,%1,%2,%3};"
                 : "+f"(c[0]), "+f"(c[1]), "+f"(c[2]), "+f"(c[3]) : "r"(a0), "r"(a1), "r"(b0));
}
__device__ __forceinline__ uint32_t lds32(uint32_t a) { uint32_t v; asm volatile("ld.shared.b32 %0, [%1];" : "=r"(v) : "r"(a) : "memory"); return v; }
__device__ __forceinline__ float ldsf(uint32_t a) { return __uint_as_float(lds32(a)); }
__device__ __forceinline__ uint2 lds64(uint32_t a) { uint2 v; asm volatile("ld.shared.v2.b32 {%0,%1}, [%2];" : "=r"(v.x), "=r"(v.y) : "r"(a) : "memory"); return v; }
__device__ __forceinline__ uint4 lds128(uint32_t a) { uint4 v; asm volatile("ld.shared.v4.b32 {%0,%1,%2,%3}, [%4];" : "=r"(v.x), "=r"(v.y), "=r"(v.z), "=r"(v.w) : "r"(a) : "memory"); return v; }
__device__ __forceinline__ void sts16(uint32_t a, uint16_t v) { asm volatile("st.shared.b16 [%0], %1;" ::"r"(a), "h"(v) : "memory"); }
__device__ __forceinline__ void stsf(uint32_t a, float v) { asm volatile("st.shared.f32 [%0], %1;" ::"r"(a), "f"(v) : "memory"); }
__device__ __forceinline__ void sts64(uint32_t a, uint32_t x, uint32_t y) { asm volatile("st.shared.v2.b32 [%0], {%1,%2};" ::"r"(a), "r"(x), "r"(y) : "memory"); }
__device__ __forceinline__ uint4 ldg_rlx128(const void* p) { uint4 v; asm volatile("ld.relaxed.gpu.global.v4.b32 {%0,%1,%2,%3}, [%4];" : "=r"(v.x), "=r"(v.y), "=r"(v.z), "=r"(v.w) : "l"(p) : "memory"); return v; }
template <int RED>
__device__ __forceinline__ void publish(void* p, float v) {
    uint32_t u = __float_as_uint(v);
    u = (u == SENT) ? 0x7FFFFFFFu : u;
    if (RED) asm volatile("red.relaxed.gpu.global.and.b32 [%0], %1;" ::"l"(p), "r"(u) : "memory");
    else asm volatile("st.relaxed.gpu.global.b32 [%0], %1;" ::"l"(p), "r"(u) : "memory");
}
__device__ __forceinline__ uint32_t nosent(float v) { const uint32_t u = __float_as_uint(v); return u == SENT ? 0x7FFFFFFFu : u; }
__device__ __forceinline__ void stg_rlx128(void* p, uint32_t x, uint32_t y, uint32_t z, uint32_t w) {
    asm volatile("st.relaxed.gpu.global.v4.b32 [%0], {%1,%2,%3,%4};" ::"l"(p), "r"(x), "r"(y), "r"(z), "r"(w) : "memory");
}
__device__ __forceinline__ uint16_t f2bf(float v) { return __bfloat16_as_ushort(__float2bfloat16_rn(v)); }
__device__ __forceinline__ float bfr(float v) { return __bfloat162float(__float2bfloat16_rn(v)); }
__device__ __forceinline__ uint32_t pack2(float lo, float hi) { return (uint32_t)f2bf(lo) | ((uint32_t)f2bf(hi) << 16); }
__device__ __forceinline__ float bflo(uint32_t u) { return __uint_as_float(u << 16); }
__device__ __forceinline__ float bfhi(uint32_t u) { return __uint_as_float(u & 0xFFFF0000u); }
__device__ __forceinline__ float shx(float v, int m) { return __shfl_xor_sync(0xFFFFFFFFu, v, m); }
__device__ __forceinline__ float pick4(float a, float b, float c, float d, int t) { float x = (t & 1) ? b : a, y = (t & 1) ? d : c; return (t & 2) ? y : x; }
__device__ __forceinline__ void bar_mma() { asm volatile("bar.sync 1, %0;" ::"n"(NMMA * 32) : "memory"); }
__device__ __forceinline__ void issue8(uint32_t dst, uint32_t dpitch, const char* src, uint32_t spitch, uint32_t bytes, uint32_t bar, uint64_t pol) {
#pragma unroll
    for (int i = 0; i < 8; i++) bulk_g2s(dst + i * dpitch, src + (size_t)i * spitch, bytes, bar, pol);
}
__device__ __forceinline__ bool has_sent(const uint4& v) { return v.x == SENT || v.y == SENT || v.z == SENT || v.w == SENT; }
__device__ __forceinline__ void ldg_rlx128_if(uint4& v, const void* p, bool pred) {
    asm volatile("{.reg .pred q; setp.ne.u32 q, %5, 0; @q ld.relaxed.gpu.global.v4.b32 {%0,%1,%2,%3}, [%4];}"
                 : "+r"(v.x), "+r"(v.y), "+r"(v.z), "+r"(v.w) : "l"(p), "r"((uint32_t)pred) : "memory");
}
template <int N, int SETS, int GAP>
__device__ __forceinline__ void gather(uint4 (&res)[N], const uint4* p, int stride) {
    if (SETS == 1) {
#pragma unroll
        for (int k = 0; k < N; k++) res[k] = ldg_rlx128(p + k * stride);
        for (unsigned it = 0;; it++) {
            bool miss = false;
#pragma unroll
            for (int k = 0; k < N; k++) { const bool m = has_sent(res[k]); miss |= m; ldg_rlx128_if(res[k], p + k * stride, m); }
            if (!__any_sync(0xFFFFFFFFu, miss)) break;
            if (it > 0x400000u) __trap();
        }
    } else {
        uint4 a[SETS][N];
#pragma unroll
        for (int s = 0; s < SETS; s++) {
            const unsigned t0 = clock();
#pragma unroll
            for (int k = 0; k < N; k++) a[s][k] = ldg_rlx128(p + k * stride);
            if (s + 1 < SETS) while ((int)((unsigned)clock() - t0) < GAP) { }
        }
#pragma unroll
        for (int k = 0; k < N; k++) res[k] = make_uint4(SENT, SENT, SENT, SENT);
        bool miss[N];
#pragma unroll
        for (int k = 0; k < N; k++) miss[k] = true;
        for (unsigned it = 0;; it++) {
            bool fin = false;
#pragma unroll
            for (int s = 0; s < SETS; s++) {
                if (!fin) {
                    bool any = false;
#pragma unroll
                    for (int k = 0; k < N; k++) {
                        if (miss[k]) res[k] = a[s][k];
                        miss[k] = miss[k] && has_sent(a[s][k]);
                        any |= miss[k];
                    }
                    fin = !__any_sync(0xFFFFFFFFu, any);
                    if (!fin) {
#pragma unroll
                        for (int k = 0; k < N; k++) ldg_rlx128_if(a[s][k], p + k * stride, miss[k]);
                    }
                }
            }
            if (fin) break;
            if (it > 0x400000u) __trap();
        }
    }
}
__device__ __forceinline__ int pos16(int k) { return (k & ~15) + ((k & 7) >> 1) * 4 + ((k >> 3) & 1) * 2 + (k & 1); }

constexpr float LOG2E = 1.4426950408889634f;

__global__ void __cluster_dims__(CS, 1, 1) __launch_bounds__(NTHREADS, 1)
fused_decode_kernel(const __nv_bfloat16* __restrict__ gx, const char* __restrict__ gk, const char* __restrict__ gv,
                    const char* __restrict__ gwq, const char* __restrict__ gwo, const char* __restrict__ gw1,
                    const char* __restrict__ gw2, __nv_bfloat16* __restrict__ gout) {
    extern __shared__ __align__(128) unsigned char smem_raw[];
    const uint32_t sb = (uint32_t)__cvta_generic_to_shared(smem_raw);
    const uint32_t bars = sb + BARS;
    const int tid = threadIdx.x, lane = tid & 31;
    const int warp = __shfl_sync(0xFFFFFFFFu, tid >> 5, 0);
    const int c = blockIdx.x / CS, r = blockIdx.x - c * CS;
    const int nK = r < 4 ? 11 : 10;
    const int nO = r < 4 ? 5 : 6;
    const int u0 = r < 5 ? 5 * r : 26;
    const int g = lane >> 2, t = lane & 3;
    const size_t kvbase = ((size_t)c * SK + (SK - WIN) + 32 * r) * 256;
    uint64_t pol = 0;
    asm volatile("createpolicy.fractional.L2::evict_first.b64 %0, 1.0;" : "=l"(pol));

    unsigned t_start;
    asm volatile("mov.u32 %0, %%globaltimer_lo;" : "=r"(t_start));
    if (warp < 12) {
        if (elect()) {
            const uint32_t b = bars + 8 * (B_WQ + warp);
            mbar_init(b, 1); mbar_expect(b, 4096);
            issue8(sb + WQ_OFF + 8 * warp * WQ_PITCH, WQ_PITCH, gwq + (size_t)(96 * r + 8 * warp) * 8192 + 512 * c, 8192, 512, b, pol);
        }
    } else if (warp >= PW0) {
        if (elect()) {
            const int p = warp - PW0;
#pragma unroll
            for (int i = 0; i < 10; i++) {
                const uint32_t b = bars + 8 * (B_K + 4 * i + p);
                mbar_init(b, 1); mbar_expect(b, 4 * i + p < 22 ? 8192 : 9216);
            }
            if (p < 3) mbar_init(bars + 8 * (B_WQDONE + p), p == 0 ? 16 : p == 1 ? NMMA : 8);
        }
    } else if (warp == 17) {
        if (elect()) {
            mbar_init(bars + 8 * B_X1, 1); mbar_init(bars + 8 * B_X2, 1); mbar_init(bars + 8 * B_X3, 1); mbar_init(bars + 8 * B_X4, 1); mbar_init(bars + 8 * B_X4S, 1);
            mbar_expect(bars + 8 * B_X1, CS * 1024); mbar_expect(bars + 8 * B_X2, CS * (nO * 32 + 16));
            mbar_expect(bars + 8 * B_X3, CS * 384); mbar_expect(bars + 8 * B_X4, CS * 384); mbar_expect(bars + 8 * B_X4S, 18 * 16);
            asm volatile("fence.mbarrier_init.release.cluster;" ::: "memory");
            mbar_init(bars + 8 * B_Q, 2); mbar_init(bars + 8 * B_O, 2);
            mbar_init(bars + 8 * B_H, 3); mbar_init(bars + 8 * B_H1, 3); mbar_init(bars + 8 * B_INIT, 1);
        }
    } else if (warp == EW0) {
        const uint4* px = reinterpret_cast<const uint4*>(gx);
        const uint4 xv0 = __ldg(px + lane), xv1 = __ldg(px + 32 + lane);
        const uint4 xv2 = lane < 8 ? __ldg(px + 64 + lane) : make_uint4(0, 0, 0, 0);
        const uint32_t w[12] = {xv0.x, xv0.y, xv0.z, xv0.w, xv1.x, xv1.y, xv1.z, xv1.w, xv2.x, xv2.y, xv2.z, xv2.w};
        float s = 0.f;
#pragma unroll
        for (int i = 0; i < 12; i++) s += bflo(w[i]) + bfhi(w[i]);
#pragma unroll
        for (int m = 16; m; m >>= 1) s += shx(s, m);
        const float mean = s * (1.0f / DM);
        float q = 0.f;
#pragma unroll
        for (int i = 0; i < 12; i++) {
            const float a = bflo(w[i]) - mean, b = bfhi(w[i]) - mean;
            if (i < 8 || lane < 8) q += a * a + b * b;
        }
#pragma unroll
        for (int m = 16; m; m >>= 1) q += shx(q, m);
        const float mb = bfr(mean), sd = bfr(sqrt_fast(bfr(bfr(q * (1.0f / DM)) + 1e-5f)));
#pragma unroll
        for (int ch = 0; ch < 3; ch++) {
            const int lc = lane + 32 * ch - 12 * r;
            if (lc >= 0 && lc < 12) {
#pragma unroll
                for (int i = 0; i < 4; i++) {
                    const float a = bflo(w[4 * ch + i]), b = bfhi(w[4 * ch + i]);
                    const int k = 8 * lc + 2 * i;
                    stsf(sb + X_S + 4 * k, a); stsf(sb + X_S + 4 * k + 4, b);
                    const uint32_t pk = pack2(__fdividef(bfr(a - mb), sd), __fdividef(bfr(b - mb), sd));
                    asm volatile("st.shared.b32 [%0], %1;" ::"r"(sb + XN_S + 2 * pos16(k)), "r"(pk) : "memory");
                }
            }
        }
        TL(1);
    } else if (warp == EW0 + 2) {
        if (lane < 24) __stcg(&g_slot3[blockIdx.x * 24 + lane], make_uint4(SENT, SENT, SENT, SENT));
        if (c < 12) {
#pragma unroll
            for (int i = 0; i < 6; i++) __stcg(&g_slot5[(r * 12 + c) * (NCTA * 2) + 32 * i + lane], make_uint4(SENT, SENT, SENT, SENT));
        }
    }
    __syncwarp();
    asm volatile("barrier.cluster.arrive.relaxed.aligned;" ::: "memory");
    if (warp >= PW0) asm volatile("bar.arrive 2, %0;" ::"n"(NTHREADS) : "memory");
    else asm volatile("bar.sync 2, %0;" ::"n"(NTHREADS) : "memory");
    if (warp == 0) TL(19);

    if (warp >= PW0) {
        asm volatile("bar.sync 3, %0;" ::"n"(NPROD * 32) : "memory");
        const int sV = nK, sO = 2 * nK, s1 = sO + nO, s2 = s1 + 6, total = s2 + 6;
        const int tauK = r < 4 ? T_K / 11 : T_K / 10, tauV = r < 4 ? T_V / 11 : T_V / 10, tauO = r < 4 ? T_O / 5 : T_O / 6;
        for (int s = warp - PW0; s < total; s += NPROD) {
            const char* src; uint32_t dst, dp, sp, bytes; int bar, ebar = -1, when;
            if (s < sO) {
                const bool isv = s >= sV;
                const int j = s - (isv ? sV : 0);
                src = (isv ? gv : gk) + kvbase + (size_t)j * (CS * 8192);
                dst = isv ? (j < 8 ? V_OFF + j * KV_STAGE : (j - 8) * KV_STAGE) : K_OFF + j * KV_STAGE;
                dp = KV_GRP; sp = 1024; bytes = 1024; bar = (isv ? B_V : B_K) + j;
                if (isv && j >= 8) ebar = B_WQDONE;
                when = isv ? T_K + j * tauV : j * tauK;
            } else if (s < s1) {
                const int j = s - sO;
                src = gwo + (size_t)(256 * c + 8 * (u0 + j)) * 1152; dst = WO_OFF + j * WR_STAGE;
                dp = WR_PITCH; sp = 1152; bytes = 1152; bar = B_WO + j; ebar = j < 2 ? B_WQDONE : B_KDONE;
                when = T_K + T_V + j * tauO;
            } else if (s < s2) {
                const int j = s - s1;
                src = gw1 + (size_t)(96 * r + 16 * j) * (FF * 2) + 576 * c; dst = W1_OFF + j * W1_STAGE;
                dp = W1_PITCH; sp = FF * 2; bytes = 576; bar = B_W1 + j; ebar = B_KDONE;
                when = T_K + T_V + T_O + j * TAU_1;
            } else {
                const int j = s - s2;
                src = gw2 + (size_t)(288 * c + 48 * r + 8 * j) * 1152; dst = W2_OFF + j * WR_STAGE;
                dp = WR_PITCH; sp = 1152; bytes = 1152; bar = B_W2 + j; ebar = B_VDONE;
                when = T_K + T_V + T_O + 6 * TAU_1 + (j < 2 ? j * TAU_2A : 2 * TAU_2A + (j - 2) * TAU_2B);
            }
            if (ebar >= 0) { mbar_wait(bars + 8 * ebar); asm volatile("fence.proxy.async.shared::cta;" ::: "memory"); }
            const int dep = s - WIN_CAP;
            if (dep >= 0) mbar_wait(bars + 8 * (dep < sV ? B_K + dep : dep < sO ? B_V + dep - sV : dep < s1 ? B_WO + dep - sO : B_W1 + dep - s1));
            const unsigned t_go = t_start + PACE_T0 + when;
            for (int it = 0; it < 100000; it++) {
                unsigned now; asm volatile("mov.u32 %0, %%globaltimer_lo;" : "=r"(now));
                if ((int)(now - t_go) >= 0) break;
            }
            if (elect()) {
                const int nh = bytes == 576 ? 2 : 1;
#pragma unroll 1
                for (int h = 0; h < nh; h++) issue8(sb + dst + 8 * h * dp, dp, src + (size_t)(8 * h) * sp, sp, bytes, bars + 8 * bar, pol);
            }
            __syncwarp();
        }
        asm volatile("barrier.cluster.wait.aligned;" ::: "memory");
    } else if (warp >= EW0) {
        const int e = warp - EW0, et = tid - EW0 * 32;
        if (e == 2) {
            asm volatile("fence.acq_rel.gpu;" ::: "memory");
            __syncwarp();
            TL(2);
            if (lane == 0) {
                unsigned v;
                asm volatile("atom.relaxed.gpu.global.add.u32 %0, [%1], 1;" : "=r"(v) : "l"(&g_arrive) : "memory");
                const unsigned target = (v / NCTA + 1) * NCTA;
                for (unsigned it = 0; (int)(++v - target) < 0; it++) {
                    asm volatile("ld.acquire.gpu.global.u32 %0, [%1];" : "=r"(v) : "l"(&g_arrive) : "memory");
                    v--;
                    if (it > 0x400000u) __trap();
                }
                mbar_arrive(bars + 8 * B_INIT);
            }
            __syncwarp();
            TL(22);
        }
        asm volatile("barrier.cluster.wait.aligned;" ::: "memory");
        if (e < 2) {
            mbar_wait(bars + 8 * B_X1);
            float a0 = 0.f, a1 = 0.f, a2 = 0.f, a3 = 0.f;
#pragma unroll
            for (int s = 0; s < CS; s++) {
                const uint4 v = lds128(sb + X1R + s * 1024 + et * 16);
                a0 += __uint_as_float(v.x); a1 += __uint_as_float(v.y); a2 += __uint_as_float(v.z); a3 += __uint_as_float(v.w);
            }
            const int w = et >> 2;
            sts64(sb + Q_S + ((w >> 3) * 4 + (et & 3)) * 80 + (w & 7) * 8, pack2(a0, a2), pack2(a1, a3));
            __syncwarp();
            if (lane == 0) mbar_arrive(bars + 8 * B_Q);
            if (e == 0) TL(3);
            mbar_wait(bars + 8 * B_X2);
            if (et < 8 * nO) {
                const int head = (u0 + (et >> 3)) >> 4;
                float m[CS], l[CS], o[CS];
#pragma unroll
                for (int s = 0; s < CS; s++) {
                    const uint2 v = lds64(sb + X2S + s * 16 + head * 8);
                    m[s] = __uint_as_float(v.x); l[s] = __uint_as_float(v.y);
                    o[s] = ldsf(sb + X2R + (s * 48 + et) * 4);
                }
                float M = m[0];
#pragma unroll
                for (int s = 1; s < CS; s++) M = fmaxf(M, m[s]);
                float L = 0.f, acc = 0.f;
#pragma unroll
                for (int s = 0; s < CS; s++) { const float ws = ex2((m[s] - M) * LOG2E); L += ws * l[s]; acc += ws * o[s]; }
                sts16(sb + O_S + 2 * et, f2bf(__fdividef(acc, L)));
            }
            __syncwarp();
            if (lane == 0) mbar_arrive(bars + 8 * B_O);
            if (e == 0) TL(4);
        }
        mbar_wait(bars + 8 * B_INIT);
        mbar_wait(bars + 8 * B_X3);
        {
            float a = 0.f;
#pragma unroll
            for (int s = 0; s < CS; s++) a += ldsf(sb + X3R + (s * 96 + et) * 4);
            publish<RED3>(reinterpret_cast<float*>(g_slot3) + (r * NCL + c) * 96 + et, a);
        }
        if (e == 0) TL(5);
        {
            uint32_t v[NCL];
            uint32_t* p3 = reinterpret_cast<uint32_t*>(g_slot3) + r * NCL * 96 + et;
#pragma unroll
            for (int k = 0; k < NCL; k++) v[k] = SENT;
            for (unsigned it = 0;; it++) {
#pragma unroll
                for (int k = 0; k < NCL; k++) POLL32_IF(v[k], p3 + k * 96);
                bool miss = false;
#pragma unroll
                for (int k = 0; k < NCL; k++) miss |= v[k] == SENT;
                if (!__any_sync(0xFFFFFFFFu, miss)) break;
                if (it > 0x400000u) __trap();
            }
            TL(6 + 14 * (e > 0) + (e > 1));
            float a4[4];
#pragma unroll
            for (int k = 0; k < 4; k++) a4[k] = (__uint_as_float(v[4 * k]) + __uint_as_float(v[4 * k + 1])) + (__uint_as_float(v[4 * k + 2]) + __uint_as_float(v[4 * k + 3]));
            const float attn = (a4[0] + a4[1]) + (a4[2] + a4[3]);
            const int lc = et;
            const float h = bfr(ldsf(sb + X_S + 4 * lc) + bfr(attn));
            sts16(sb + H_S + 2 * pos16(lc), f2bf(h));
            stsf(sb + HF_S + 4 * lc, h);
            __syncwarp();
            if (lane == 0) mbar_arrive(bars + 8 * B_H);
            TL(53 + e);
            const float k0 = __shfl_sync(0xFFFFFFFFu, h, 0);
            float s = h - k0, q = s * s;
#pragma unroll
            for (int m = 16; m; m >>= 1) { s += shx(s, m); q += shx(q, m); }
            if (lane < CS) st_async4(mapa(sb + X4S + (r * 3 + e) * 16, lane), k0, s, q, 0.f, mapa(bars + 8 * B_X4S, lane));
        }
        {
            mbar_wait(bars + 8 * B_X4S);
            if (e == 0) TL(26);
            const float kc = ldsf(sb + X4S);
            const uint4 st = lds128(sb + X4S + (lane < 18 ? lane : 0) * 16);
            const float dk = __uint_as_float(st.x) - kc, gs = __uint_as_float(st.y);
            float s = lane < 18 ? gs + 32.0f * dk : 0.f;
            float q = lane < 18 ? __uint_as_float(st.z) + dk * (2.0f * gs + 32.0f * dk) : 0.f;
#pragma unroll
            for (int m = 16; m; m >>= 1) { s += shx(s, m); q += shx(q, m); }
            const float dm = s * (1.0f / DM);
            const float var = fmaxf(q * (1.0f / DM) - dm * dm, 0.f);
            const float mb = bfr(kc + dm), rsd = __fdividef(1.0f, bfr(sqrt_fast(bfr(bfr(var) + 1e-5f))));
            mbar_wait(bars + 8 * B_X4);
            if (e == 0) TL(7);
            const int f = 16 * e + (lane >> 1);
            float s1 = 0.f, s2 = 0.f;
#pragma unroll
            for (int i = 0; i < 3; i++) {
                const uint2 v = lds64(sb + X4R + ((3 * (lane & 1) + i) * 48 + f) * 8);
                s1 += __uint_as_float(v.x); s2 += __uint_as_float(v.y);
            }
            float pre = s1 - mb * s2;
            pre = bfr((pre + shx(pre, 1)) * rsd);
            const float act = __fdividef(pre, 1.0f + ex2(-pre * LOG2E));
            if (!(lane & 1)) sts16(sb + H1_S + 2 * f, f2bf(act));
            __syncwarp();
            if (lane == 0) mbar_arrive(bars + 8 * B_H1);
            TL(56 + e);
        }
        if (e == 0 && c < 12) {
            TL(8);
            mbar_wait(bars + 8 * B_H);
            const int lc = 8 * c + 4 * (lane & 1) + 2 * (lane >> 4) + ((lane >> 3) & 1);
            const float hres = ldsf(sb + HF_S + 4 * lc);
            uint4 v[6];
            gather<6, 1, 0>(v, g_slot5 + (r * 12 + c) * (NCTA * 2) + lane, 32);
            TL(9);
#define SUM6(f) (((__uint_as_float(v[0].f) + __uint_as_float(v[1].f)) + (__uint_as_float(v[2].f) + __uint_as_float(v[3].f))) + (__uint_as_float(v[4].f) + __uint_as_float(v[5].f)))
            const float a0 = SUM6(x), a1 = SUM6(y), a2 = SUM6(z), a3 = SUM6(w);
#undef SUM6
            const bool h16 = lane & 16, h8 = lane & 8;
            const float b0 = (h16 ? a2 : a0) + shx(h16 ? a0 : a2, 16), b1 = (h16 ? a3 : a1) + shx(h16 ? a1 : a3, 16);
            float y = (h8 ? b1 : b0) + shx(h8 ? b0 : b1, 8);
            y += shx(y, 4); y += shx(y, 2);
            if (!(lane & 6)) gout[96 * r + lc] = __float2bfloat16_rn(hres + bfr(y));
            TL(10);
        }
    } else {
        const int w = warp;
        if (w < 16) {
            uint2 b[6];
#pragma unroll
            for (int ks = 0; ks < 6; ks++) b[ks] = lds64(sb + XN_S + (ks * 4 + t) * 8);
            float acc[2][4] = {};
            const uint32_t ab = sb + WQ_OFF + ((lane & 7) + 8 * (lane >> 4)) * WQ_PITCH + (2 * w + ((lane >> 3) & 1)) * 16;
#pragma unroll
            for (int ks = 0; ks < 6; ks++) {
                mbar_wait(bars + 8 * (B_WQ + 2 * ks)); mbar_wait(bars + 8 * (B_WQ + 2 * ks + 1));
                uint32_t a[4]; ldsm4t(a, ab + ks * WQ_STAGE);
                mma16(acc[ks & 1], a, b[ks].x, b[ks].y);
            }
            const float c0 = acc[0][0] + acc[1][0], c2 = acc[0][2] + acc[1][2];
            if (w == 0) TL(11);
            asm volatile("barrier.cluster.wait.aligned;" ::: "memory");
            const uint32_t da = sb + X1R + r * 1024 + (w * 8 + g) * 8;
            st_async2(mapa(da, t), c0, c2, mapa(bars + 8 * B_X1, t));
            if (t < 2) st_async2(mapa(da, t + 4), c0, c2, mapa(bars + 8 * B_X1, t + 4));
            if (lane == 0) mbar_arrive(bars + 8 * B_WQDONE);
        } else {
            asm volatile("barrier.cluster.wait.aligned;" ::: "memory");
        }
        const int head = t & 1, half = t >> 1;
        float sc[2];
        {
            mbar_wait(bars + 8 * B_Q);
            uint32_t qb[16];
#pragma unroll
            for (int j = 0; j < 4; j++) {
                const uint4 v = lds128(sb + Q_S + ((g & 1) * 4 + t) * 80 + j * 16);
                qb[4 * j] = v.x; qb[4 * j + 1] = v.y; qb[4 * j + 2] = v.z; qb[4 * j + 3] = v.w;
            }
#pragma unroll
            for (int it = 0; it < 2; it++) {
                const int tau = w + NMMA * it;
                sc[it] = -INFINITY;
                if (tau < 2 * nK) {
                    mbar_wait(bars + 8 * (B_K + (tau >> 1)));
                    const uint32_t ab = sb + K_OFF + (tau >> 1) * KV_STAGE + (lane & 7) * KV_GRP + ((tau & 1) * 2 + ((lane >> 3) & 1)) * 256 + (lane >> 4) * 16;
                    float acc[2][4] = {};
#pragma unroll
                    for (int ks = 0; ks < 8; ks++) {
                        uint32_t a[4]; ldsm4(a, ab + ks * 32);
                        mma16(acc[ks & 1], a, qb[2 * ks], qb[2 * ks + 1]);
                    }
                    const float raw = pick4(acc[0][0] + acc[1][0], acc[0][1] + acc[1][1], acc[0][2] + acc[1][2], acc[0][3] + acc[1][3], t);
                    sc[it] = bfr(bfr(raw) * 0.08838834764831845f);
                }
            }
        }
        float M = fmaxf(sc[0], sc[1]);
#pragma unroll
        for (int m = 2; m <= 16; m <<= 1) M = fmaxf(M, shx(M, m));
        if (lane < 2) stsf(sb + WMAX + (2 * w + lane) * 4, M);
        if (lane == 0) mbar_arrive(bars + 8 * B_KDONE);
        if (w == 0) TL(12);
        bar_mma();
        M = ldsf(sb + WMAX + lane * 4);
        if (lane < 4) M = fmaxf(M, ldsf(sb + WMAX + (32 + lane) * 4));
#pragma unroll
        for (int m = 2; m <= 16; m <<= 1) M = fmaxf(M, shx(M, m));
        {
            float ls = 0.f;
#pragma unroll
            for (int it = 0; it < 2; it++) {
                const int tau = w + NMMA * it;
                if (tau < 2 * nK) {
                    const __nv_bfloat16 pb = __float2bfloat16_rn(ex2((sc[it] - M) * LOG2E));
                    ls += __bfloat162float(pb);
                    sts16(sb + P_S + head * 704 + (tau * 16 + (g >> 1) * 4 + half * 2 + (g & 1)) * 2, __bfloat16_as_ushort(pb));
                }
            }
#pragma unroll
            for (int m = 2; m <= 16; m <<= 1) ls += shx(ls, m);
            if (lane < 2) stsf(sb + WSUM + (2 * w + lane) * 4, ls);
        }
        bar_mma();
        if (w == 8) {
            float L = ldsf(sb + WSUM + lane * 4);
            if (lane < 4) L += ldsf(sb + WSUM + (32 + lane) * 4);
#pragma unroll
            for (int m = 2; m <= 16; m <<= 1) L += shx(L, m);
            const float Mo = shx(M, 1), Lo = shx(L, 1);
            if (lane < CS) st_async4(mapa(sb + X2S + r * 16, lane), head ? Mo : M, head ? Lo : L, head ? M : Mo, head ? L : Lo, mapa(bars + 8 * B_X2, lane));
            TL(13);
        }
        if (w < 8) {
            float acc[2][4] = {};
            const uint32_t ao = sb + (lane & 7) * KV_GRP + (lane >> 4) * 256 + (2 * w + ((lane >> 3) & 1)) * 16;
            const uint32_t pb = sb + P_S + (g & 1) * 704 + t * 8;
#pragma unroll
            for (int j = 0; j < 11; j++) {
                if (j < nK) {
                    const uint2 b0 = lds64(pb + j * 64), b1 = lds64(pb + j * 64 + 32);
                    mbar_wait(bars + 8 * (B_V + j));
                    const uint32_t ab = ao + (j < 8 ? V_OFF + j * KV_STAGE : (j - 8) * KV_STAGE);
                    uint32_t a0[4], a1[4];
                    ldsm4t(a0, ab); ldsm4t(a1, ab + 512);
                    mma16(acc[0], a0, b0.x, b0.y);
                    mma16(acc[1], a1, b1.x, b1.y);
                    if (j == 6 && lane == 0) mbar_arrive(bars + 8 * B_VDONE);
                }
            }
            const float val = pick4(acc[0][0] + acc[1][0], acc[0][1] + acc[1][1], acc[0][2] + acc[1][2], acc[0][3] + acc[1][3], t);
            const int u = 16 * head + 2 * w + half;
            const int dest = u < 20 ? u / 5 : (u < 26 ? 4 : 5);
            const int ud = u - (dest < 5 ? 5 * dest : 26);
            st_async1(mapa(sb + X2R + (r * 48 + ud * 8 + g) * 4, dest), val, mapa(bars + 8 * B_X2, dest));
            if (w == 0) TL(14);
        }
        const int rd = w / 3, jd = w - 3 * rd;
        const uint32_t wro = (lane & 7) * WR_PITCH + (4 * w + (lane >> 3)) * 16;
        {
            mbar_wait(bars + 8 * B_O);
            uint32_t b[6];
#pragma unroll
            for (int u = 0; u < 6; u++) b[u] = lds32(sb + O_S + (8 * u + 2 * t) * 2);
            float accA[2][4] = {}, accB[2][4] = {};
#pragma unroll
            for (int u = 0; u < 6; u++) {
                if (u < nO) {
                    mbar_wait(bars + 8 * (B_WO + u));
                    uint32_t a[4]; ldsm4t(a, sb + WO_OFF + u * WR_STAGE + wro);
                    mma8(accA[u & 1], a[0], a[1], b[u]);
                    mma8(accB[u & 1], a[2], a[3], b[u]);
                }
            }
            const float val = pick4(accA[0][0] + accA[1][0], accA[0][2] + accA[1][2], accB[0][0] + accB[1][0], accB[0][2] + accB[1][2], t);
            st_async1(mapa(sb + X3R + (r * 96 + 32 * jd + 8 * t + g) * 4, rd), val, mapa(bars + 8 * B_X3, rd));
            if (w == 0) TL(15);
            if (w == 17) TL(23);
        }
        {
            uint32_t a[6][4];
            const uint32_t ab = sb + W1_OFF + ((lane & 7) + 8 * (lane >> 4)) * W1_PITCH + (2 * w + ((lane >> 3) & 1)) * 16;
#pragma unroll
            for (int ks = 0; ks < 6; ks++) { mbar_wait(bars + 8 * (B_W1 + ks)); ldsm4t(a[ks], ab + ks * W1_STAGE); }
            if (w == 0) TL(16);
            mbar_wait(bars + 8 * B_H);
            if (w == 0) TL(28);
            float acc[2][4] = {};
#pragma unroll
            for (int ks = 0; ks < 6; ks++) {
                uint2 b = lds64(sb + H_S + (ks * 4 + t) * 8);
                if (g & 1) b = make_uint2(0x3F803F80u, 0x3F803F80u);
                mma16(acc[ks & 1], a[ks], b.x, b.y);
            }
            if (t < 2) {
                const float s1 = t ? acc[0][2] + acc[1][2] : acc[0][0] + acc[1][0];
                const float s2 = t ? acc[0][3] + acc[1][3] : acc[0][1] + acc[1][1];
                st_async2(mapa(sb + X4R + (r * 48 + 16 * jd + 8 * t + g) * 8, rd), s1, s2, mapa(bars + 8 * B_X4, rd));
            }
            __syncwarp();
            if (w == 0) TL(24);
            if (w == 17) TL(25);
        }
        {
            uint32_t a[5][4];
#pragma unroll
            for (int u = 0; u < 5; u++) { mbar_wait(bars + 8 * (B_W2 + u)); ldsm4t(a[u], sb + W2_OFF + u * WR_STAGE + wro); }
            if (w == 0) TL(27);
            mbar_wait(bars + 8 * B_H1);
            if (w == 0) TL(29);
            uint32_t b[6];
#pragma unroll
            for (int u = 0; u < 6; u++) b[u] = lds32(sb + H1_S + (8 * u + 2 * t) * 2);
            float accA[2][4] = {}, accB[2][4] = {};
#pragma unroll
            for (int u = 0; u < 5; u++) { mma8(accA[u & 1], a[u][0], a[u][1], b[u]); mma8(accB[u & 1], a[u][2], a[u][3], b[u]); }
            mbar_wait(bars + 8 * (B_W2 + 5));
            if (w == 0) TL(17);
            uint32_t al[4]; ldsm4t(al, sb + W2_OFF + 5 * WR_STAGE + wro);
            mma8(accA[1], al[0], al[1], b[5]); mma8(accB[1], al[2], al[3], b[5]);
            const float val = pick4(accA[0][0] + accA[1][0], accA[0][2] + accA[1][2], accB[0][0] + accB[1][0], accB[0][2] + accB[1][2], t);
            publish<RED5>(reinterpret_cast<float*>(g_slot5) + ((4 * w + t) * NCTA + blockIdx.x) * 8 + g, val);
            TL(32 + w);
        }
    }
}

}

extern "C" void kernel_launch(void* const* d_in, const int* in_sizes, int n_in, void* d_out, int out_size) {
    (void)in_sizes; (void)n_in; (void)out_size;
    static bool configured = false;
    if (!configured) {
        cudaFuncSetAttribute(fused_decode_kernel, cudaFuncAttributeMaxDynamicSharedMemorySize, SMEM_BYTES);
        configured = true;
    }
    fused_decode_kernel<<<NCTA, NTHREADS, SMEM_BYTES>>>(
        (const __nv_bfloat16*)d_in[0], (const char*)d_in[1], (const char*)d_in[2], (const char*)d_in[3],
        (const char*)d_in[4], (const char*)d_in[6], (const char*)d_in[7], (__nv_bfloat16*)d_out);
}
```

```cpp
#include <cuda_runtime.h>
#include <cuda_bf16.h>
#include <stdint.h>

namespace {

constexpr int DM = 576, SK = 8192, WIN = 2048, FF = 4608;
constexpr int CS = 6, NCL = 16, NCTA = CS * NCL;
constexpr int NMMA = 18;
constexpr int EW0 = 18;
constexpr int PW0 = 21, NPROD = 4;
constexpr int NTHREADS = (PW0 + NPROD) * 32;

constexpr int PACE_T0 = 775, T_K = 2650, T_V = 2780, T_O = 1740, TAU_1 = 276, TAU_2A = 290, TAU_2B = 250, WIN_CAP = 10, SKEW = 0, ATOM_TH = 8, ATOM_TH5 = 4;
#define RED3 1
#define RED5 1
#define X5MODE 0
#define KV_CONTIG 0
#define GUARD 1
#define LASTK8 0
#define NAMED_H 1
#define USE_EVICT_FIRST 1

constexpr int WQ_PITCH = 528, KV_GRP = 1040, KV_STAGE = 8 * KV_GRP, WR_PITCH = 1168, WR_STAGE = 8 * WR_PITCH;
constexpr int W1_PITCH = 592, W1_STAGE = 16 * W1_PITCH, WQ_STAGE = 16 * WQ_PITCH;
constexpr int WQ_OFF = 0;
constexpr int K_OFF = 96 * WQ_PITCH;
constexpr int V_OFF = K_OFF + 11 * KV_STAGE;
constexpr int RING_END = V_OFF + 8 * KV_STAGE;
constexpr int WO_OFF = 3 * KV_STAGE;
constexpr int W1_OFF = WO_OFF + 6 * WR_STAGE;
constexpr int W2_OFF = W1_OFF + 6 * W1_STAGE;
static_assert(W2_OFF + 6 * WR_STAGE <= V_OFF + 7 * KV_STAGE, "w2 must only overlap V stages 0..6");
constexpr int X1R = RING_END;
constexpr int X2R = X1R + 6144;
constexpr int X2S = X2R + 1152;
constexpr int X3R = X2S + 96;
constexpr int X4R = X3R + 2304;
constexpr int X4S = X4R + 2304;
constexpr int Q_S = X4S + 288;
constexpr int XN_S = Q_S + 640;
constexpr int X_S = XN_S + 192;
constexpr int P_S = X_S + 384;
constexpr int WMAX = P_S + 1408;
constexpr int WSUM = WMAX + 160;
constexpr int O_S = WSUM + 160;
constexpr int H_S = O_S + 96;
constexpr int HF_S = H_S + 192;
constexpr int H1_S = HF_S + 384;
constexpr int ONES_S = H1_S + 96;
constexpr int X5R = ONES_S + 192;
constexpr int BARS = X5R + 2304;
constexpr int B_WQ = 0, B_K = 12, B_V = 23, B_WO = 34, B_W1 = 40, B_W2 = 46;
constexpr int B_WQDONE = 52, B_KDONE = 53, B_VDONE = 54;
constexpr int B_X1 = 55, B_X2 = 56, B_X3 = 57, B_X4 = 58, B_X4S = 59;
constexpr int B_Q = 60, B_O = 61, B_H = 62, B_H1 = 63, B_INIT = 64, B_X5 = 65;
constexpr int NBAR = 66;
constexpr int SMEM_BYTES = BARS + NBAR * 8;
static_assert(BARS % 8 == 0 && X2S % 16 == 0 && Q_S % 16 == 0 && X4R % 16 == 0 && X1R % 16 == 0, "align");
static_assert(SMEM_BYTES <= 232448, "smem");

constexpr uint32_t SENT = 0xFFFFFFFFu;

constexpr int NOWN = 72;
constexpr int STR3 = 3, STR5 = 24;
__device__ __align__(256) uint4 g_slot3[CS * NCL * STR3 * 8];
__device__ __align__(256) uint4 g_slot5[NOWN * STR5 * 8];
__device__ __align__(256) unsigned g_arrive;
#define G_ARRIVE (&g_arrive)

#define TL(i) do { } while (0)

__device__ __forceinline__ void mbar_init(uint32_t b, uint32_t c) { asm volatile("mbarrier.init.shared::cta.b64 [%0], %1;" ::"r"(b), "r"(c) : "memory"); }
__device__ __forceinline__ void mbar_expect(uint32_t b, uint32_t bytes) { asm volatile("mbarrier.arrive.expect_tx.shared::cta.b64 _, [%0], %1;" ::"r"(b), "r"(bytes) : "memory"); }
__device__ __forceinline__ void mbar_arrive(uint32_t b) { asm volatile("mbarrier.arrive.shared::cta.b64 _, [%0];" ::"r"(b) : "memory"); }
__device__ __forceinline__ void mbar_wait(uint32_t b) {
    asm volatile("{\n.reg .pred p;\n.reg .u32 n;\nmov.u32 n, 0;\n"
                 "W_LOOP:\nmbarrier.try_wait.parity.shared::cta.b64 p, [%0], 0;\n@p bra W_DONE;\n"
                 "add.u32 n, n, 1;\nsetp.lt.u32 p, n, 0x400000;\n@p bra W_LOOP;\ntrap;\nW_DONE:\n}" ::"r"(b) : "memory");
}
__device__ __forceinline__ bool elect() { uint32_t p; asm volatile("{.reg .pred P; elect.sync _|P, 0xffffffff; selp.u32 %0,1,0,P;}" : "=r"(p)); return p; }
__device__ __forceinline__ float ex2(float x) { float y; asm("ex2.approx.ftz.f32 %0, %1;" : "=f"(y) : "f"(x)); return y; }
__device__ __forceinline__ float sqrt_fast(float x) { float y; asm("sqrt.approx.f32 %0, %1;" : "=f"(y) : "f"(x)); return y; }
__device__ __forceinline__ void bulk_g2s(uint32_t dst, const void* src, uint32_t bytes, uint32_t bar, uint64_t pol) {
    asm volatile("cp.async.bulk.shared::cluster.global.mbarrier::complete_tx::bytes.L2::cache_hint [%0], [%1], %2, [%3], %4;" ::"r"(dst), "l"(src), "r"(bytes), "r"(bar), "l"(pol) : "memory");
}
__device__ __forceinline__ uint32_t mapa(uint32_t a, uint32_t rank) { uint32_t r; asm("mapa.shared::cluster.u32 %0, %1, %2;" : "=r"(r) : "r"(a), "r"(rank)); return r; }
__device__ __forceinline__ void st_async1(uint32_t a, float v, uint32_t bar) { asm volatile("st.async.shared::cluster.mbarrier::complete_tx::bytes.b32 [%0], %1, [%2];" ::"r"(a), "r"(__float_as_uint(v)), "r"(bar) : "memory"); }
__device__ __forceinline__ void st_async2(uint32_t a, float x, float y, uint32_t bar) { asm volatile("st.async.shared::cluster.mbarrier::complete_tx::bytes.v2.b32 [%0], {%1,%2}, [%3];" ::"r"(a), "r"(__float_as_uint(x)), "r"(__float_as_uint(y)), "r"(bar) : "memory"); }
__device__ __forceinline__ void st_async4(uint32_t a, float x, float y, float z, float w, uint32_t bar) { asm volatile("st.async.shared::cluster.mbarrier::complete_tx::bytes.v4.b32 [%0], {%1,%2,%3,%4}, [%5];" ::"r"(a), "r"(__float_as_uint(x)), "r"(__float_as_uint(y)), "r"(__float_as_uint(z)), "r"(__float_as_uint(w)), "r"(bar) : "memory"); }
__device__ __forceinline__ void ldsm4(uint32_t (&r)[4], uint32_t a) { asm volatile("ldmatrix.sync.aligned.m8n8.x4.shared.b16 {%0,%1,%2,%3}, [%4];" : "=r"(r[0]), "=r"(r[1]), "=r"(r[2]), "=r"(r[3]) : "r"(a) : "memory"); }
__device__ __forceinline__ void ldsm4t(uint32_t (&r)[4], uint32_t a) { asm volatile("ldmatrix.sync.aligned.m8n8.x4.trans.shared.b16 {%0,%1,%2,%3}, [%4];" : "=r"(r[0]), "=r"(r[1]), "=r"(r[2]), "=r"(r[3]) : "r"(a) : "memory"); }
__device__ __forceinline__ void mma16(float (&c)[4], const uint32_t (&a)[4], uint32_t b0, uint32_t b1) {
    asm volatile("mma.sync.aligned.m16n8k16.row.col.f32.bf16.bf16.f32 {%0,%1,%2,%3}, {%4,%5,%6,%7}, {%8,%9}, {%0,%1,%2,%3};"
                 : "+f"(c[0]), "+f"(c[1]), "+f"(c[2]), "+f"(c[3]) : "r"(a[0]), "r"(a[1]), "r"(a[2]), "r"(a[3]), "r"(b0), "r"(b1));
}
__device__ __forceinline__ void mma8(float (&c)[4], uint32_t a0, uint32_t a1, uint32_t b0) {
    asm volatile("mma.sync.aligned.m16n8k8.row.col.f32.bf16.bf16.f32 {%0,%1,%2,%3}, {%4,%5}, {%6}, {%0,%1,%2,%3};"
                 : "+f"(c[0]), "+f"(c[1]), "+f"(c[2]), "+f"(c[3]) : "r"(a0), "r"(a1), "r"(b0));
}
__device__ __forceinline__ uint32_t lds32(uint32_t a) { uint32_t v; asm volatile("ld.shared.b32 %0, [%1];" : "=r"(v) : "r"(a) : "memory"); return v; }
__device__ __forceinline__ float ldsf(uint32_t a) { return __uint_as_float(lds32(a)); }
__device__ __forceinline__ uint2 lds64(uint32_t a) { uint2 v; asm volatile("ld.shared.v2.b32 {%0,%1}, [%2];" : "=r"(v.x), "=r"(v.y) : "r"(a) : "memory"); return v; }
__device__ __forceinline__ uint4 lds128(uint32_t a) { uint4 v; asm volatile("ld.shared.v4.b32 {%0,%1,%2,%3}, [%4];" : "=r"(v.x), "=r"(v.y), "=r"(v.z), "=r"(v.w) : "r"(a) : "memory"); return v; }
__device__ __forceinline__ void sts16(uint32_t a, uint16_t v) { asm volatile("st.shared.b16 [%0], %1;" ::"r"(a), "h"(v) : "memory"); }
__device__ __forceinline__ void stsf(uint32_t a, float v) { asm volatile("st.shared.f32 [%0], %1;" ::"r"(a), "f"(v) : "memory"); }
__device__ __forceinline__ void sts64(uint32_t a, uint32_t x, uint32_t y) { asm volatile("st.shared.v2.b32 [%0], {%1,%2};" ::"r"(a), "r"(x), "r"(y) : "memory"); }
__device__ __forceinline__ uint4 ldg_rlx128(const void* p) { uint4 v; asm volatile("ld.relaxed.gpu.global.v4.b32 {%0,%1,%2,%3}, [%4];" : "=r"(v.x), "=r"(v.y), "=r"(v.z), "=r"(v.w) : "l"(p) : "memory"); return v; }
template <int RED>
__device__ __forceinline__ void publish(void* p, float v) {
    uint32_t u = __float_as_uint(v);
    u = (u == SENT) ? 0x7FFFFFFFu : u;
    if (RED) asm volatile("red.relaxed.gpu.global.and.b32 [%0], %1;" ::"l"(p), "r"(u) : "memory");
    else asm volatile("st.relaxed.gpu.global.b32 [%0], %1;" ::"l"(p), "r"(u) : "memory");
}
__device__ __forceinline__ uint32_t pack2(float lo, float hi) { uint32_t d; asm("cvt.rn.bf16x2.f32 %0, %1, %2;" : "=r"(d) : "f"(hi), "f"(lo)); return d; }
__device__ __forceinline__ uint16_t f2bf(float v) { return (uint16_t)pack2(v, 0.f); }
__device__ __forceinline__ float bfr(float v) { return __uint_as_float(pack2(0.f, v)); }
template <typename T> __device__ __forceinline__ T* pin(T* p) { asm volatile("" : "+l"(p)); return p; }
__device__ __forceinline__ uint32_t pin(uint32_t a) { asm volatile("" : "+r"(a)); return a; }
__device__ __forceinline__ float bflo(uint32_t u) { return __uint_as_float(u << 16); }
__device__ __forceinline__ float bfhi(uint32_t u) { return __uint_as_float(u & 0xFFFF0000u); }
__device__ __forceinline__ float shx(float v, int m) { return __shfl_xor_sync(0xFFFFFFFFu, v, m); }
__device__ __forceinline__ float pick4(float a, float b, float c, float d, int t) { float x = (t & 1) ? b : a, y = (t & 1) ? d : c; return (t & 2) ? y : x; }
__device__ __forceinline__ void bar_mma() { asm volatile("bar.sync 1, %0;" ::"n"(NMMA * 32) : "memory"); }
__device__ __forceinline__ void issue8(uint32_t dst, uint32_t dpitch, const char* src, uint32_t spitch, uint32_t bytes, uint32_t bar, uint64_t pol) {
#pragma unroll
    for (int i = 0; i < 8; i++) bulk_g2s(dst + i * dpitch, src + (size_t)i * spitch, bytes, bar, pol);
}
__device__ __forceinline__ bool has_sent(const uint4& v) { return v.x == SENT || v.y == SENT || v.z == SENT || v.w == SENT; }
__device__ __forceinline__ void ldg_rlx128_if(uint4& v, const void* p, bool pred) {
    asm volatile("{.reg .pred q; setp.ne.u32 q, %5, 0; @q ld.relaxed.gpu.global.v4.b32 {%0,%1,%2,%3}, [%4];}"
                 : "+r"(v.x), "+r"(v.y), "+r"(v.z), "+r"(v.w) : "l"(p), "r"((uint32_t)pred) : "memory");
}
__device__ __forceinline__ uint32_t atom_read(uint32_t* p) { uint32_t v; asm volatile("atom.relaxed.gpu.global.or.b32 %0, [%1], 0;" : "=r"(v) : "l"(p) : "memory"); return v; }
__device__ __forceinline__ uint32_t ld_read(const uint32_t* p) { uint32_t v; asm volatile("ld.relaxed.gpu.global.b32 %0, [%1];" : "=r"(v) : "l"(p) : "memory"); return v; }
__device__ __forceinline__ void ld_read_if(uint32_t& v, const uint32_t* p) { asm volatile("{.reg .pred q; setp.eq.u32 q, %0, 0xFFFFFFFF; @q ld.relaxed.gpu.global.b32 %0, [%1];}" : "+r"(v) : "l"(p) : "memory"); }
template <int N>
__device__ __forceinline__ float gather_sum(uint32_t* p, int stride, int atom_th) {
    uint32_t v[N];
#pragma unroll
    for (int k = 0; k < N; k++) v[k] = ld_read(p + k * stride);
    for (unsigned it = 0;; it++) {
        float a[N / 4];
#pragma unroll
        for (int k = 0; k < N / 4; k++) a[k] = (__uint_as_float(v[4 * k]) + __uint_as_float(v[4 * k + 1])) + (__uint_as_float(v[4 * k + 2]) + __uint_as_float(v[4 * k + 3]));
        float y = (a[0] + a[1]) + (a[2] + a[3]);
        if (N == 24) y += a[N / 4 - 2] + a[N / 4 - 1];
        if (!__any_sync(0xFFFFFFFFu, y != y)) return y;
        uint32_t m = 0;
#pragma unroll
        for (int k = 0; k < N; k++) m |= (v[k] == SENT ? 1u : 0u) << k;
        m = __reduce_or_sync(0xFFFFFFFFu, m);
        if (m == 0) return y;
        if (__popc(m) <= atom_th) {
#pragma unroll
            for (int k = 0; k < N; k++) if (m >> k & 1) v[k] = atom_read(p + k * stride);
        } else {
#pragma unroll
            for (int k = 0; k < N; k++) ld_read_if(v[k], p + k * stride);
        }
        if (it > 0x400000u) __trap();
    }
}
__device__ __forceinline__ int pos16(int k) { return (k & ~15) + ((k & 7) >> 1) * 4 + ((k >> 3) & 1) * 2 + (k & 1); }

constexpr float LOG2E = 1.4426950408889634f;

__global__ void __cluster_dims__(CS, 1, 1) __launch_bounds__(NTHREADS, 1)
fused_decode_kernel(const __nv_bfloat16* __restrict__ gx, const char* __restrict__ gk, const char* __restrict__ gv,
                    const char* __restrict__ gwq, const char* __restrict__ gwo, const char* __restrict__ gw1,
                    const char* __restrict__ gw2, __nv_bfloat16* __restrict__ gout) {
    extern __shared__ __align__(128) unsigned char smem_raw[];
    const uint32_t sb = (uint32_t)__cvta_generic_to_shared(smem_raw);
    const uint32_t bars = sb + BARS;
    const int tid = threadIdx.x, lane = tid & 31;
    const int warp = __shfl_sync(0xFFFFFFFFu, tid >> 5, 0);
    const int c = blockIdx.x / CS, r = blockIdx.x - c * CS;
    const int nK = r < 4 ? 11 : 10;
    const int nO = r < 4 ? 5 : 6;
    const int u0 = r < 5 ? 5 * r : 26;
    const int g = lane >> 2, t = lane & 3;
    const size_t kvbase = ((size_t)c * SK + (SK - WIN) + 32 * r) * 256;
    constexpr int KV_STEP = CS * 8192;
    uint64_t pol = 0;
    asm volatile("createpolicy.fractional.L2::evict_first.b64 %0, 1.0;" : "=l"(pol));

    unsigned t_start;
    asm volatile("mov.u32 %0, %%globaltimer_lo;" : "=r"(t_start));
    if (warp < 12) {
        if (elect()) {
            const uint32_t b = bars + 8 * (B_WQ + warp);
            mbar_init(b, 1); mbar_expect(b, 4096);
            issue8(sb + WQ_OFF + 8 * warp * WQ_PITCH, WQ_PITCH, gwq + (size_t)(96 * r + 8 * warp) * 8192 + 512 * c, 8192, 512, b, pol);
        }
    } else if (warp >= PW0) {
        if (elect()) {
            const int p = warp - PW0;
#pragma unroll
            for (int i = 0; i < 10; i++) {
                const uint32_t b = bars + 8 * (B_K + 4 * i + p);
                mbar_init(b, 1); mbar_expect(b, 4 * i + p < 22 ? 8192 : 9216);
            }
            if (p < 3) mbar_init(bars + 8 * (B_WQDONE + p), p == 0 ? 16 : p == 1 ? NMMA : 8);
        }
    } else if (warp == 16) {
        if (lane < 24) sts64(sb + ONES_S + lane * 8, 0x3F803F80u, 0x3F803F80u);
    } else if (warp == 17) {
        if (elect()) {
            mbar_init(bars + 8 * B_X1, 1); mbar_init(bars + 8 * B_X2, 1); mbar_init(bars + 8 * B_X3, 1); mbar_init(bars + 8 * B_X4, 1); mbar_init(bars + 8 * B_X4S, 1);
            mbar_expect(bars + 8 * B_X1, CS * 1024); mbar_expect(bars + 8 * B_X2, CS * (nO * 32 + 16));
            mbar_expect(bars + 8 * B_X3, CS * 384); mbar_expect(bars + 8 * B_X4, CS * 384); mbar_expect(bars + 8 * B_X4S, 18 * 16);
            asm volatile("fence.mbarrier_init.release.cluster;" ::: "memory");
            mbar_init(bars + 8 * B_Q, 2); mbar_init(bars + 8 * B_O, 2);
            mbar_init(bars + 8 * B_H, 3); mbar_init(bars + 8 * B_H1, 3); mbar_init(bars + 8 * B_INIT, 1);
        }
    } else if (warp == EW0) {
        const uint4* px = reinterpret_cast<const uint4*>(gx);
        const uint4 xv0 = __ldg(px + lane), xv1 = __ldg(px + 32 + lane);
        const uint4 xv2 = lane < 8 ? __ldg(px + 64 + lane) : make_uint4(0, 0, 0, 0);
        const uint32_t w[12] = {xv0.x, xv0.y, xv0.z, xv0.w, xv1.x, xv1.y, xv1.z, xv1.w, xv2.x, xv2.y, xv2.z, xv2.w};
        float s = 0.f;
#pragma unroll
        for (int i = 0; i < 12; i++) s += bflo(w[i]) + bfhi(w[i]);
#pragma unroll
        for (int m = 16; m; m >>= 1) s += shx(s, m);
        const float mean = s * (1.0f / DM);
        float q = 0.f;
#pragma unroll
        for (int i = 0; i < 12; i++) {
            const float a = bflo(w[i]) - mean, b = bfhi(w[i]) - mean;
            if (i < 8 || lane < 8) q += a * a + b * b;
        }
#pragma unroll
        for (int m = 16; m; m >>= 1) q += shx(q, m);
        const float mb = bfr(mean), sd = bfr(sqrt_fast(bfr(bfr(q * (1.0f / DM)) + 1e-5f)));
#pragma unroll
        for (int ch = 0; ch < 3; ch++) {
            const int lc = lane + 32 * ch - 12 * r;
            if (lc >= 0 && lc < 12) {
#pragma unroll
                for (int i = 0; i < 4; i++) {
                    const float a = bflo(w[4 * ch + i]), b = bfhi(w[4 * ch + i]);
                    const int k = 8 * lc + 2 * i;
                    stsf(sb + X_S + 4 * k, a); stsf(sb + X_S + 4 * k + 4, b);
                    const uint32_t pk = pack2(__fdividef(bfr(a - mb), sd), __fdividef(bfr(b - mb), sd));
                    asm volatile("st.shared.b32 [%0], %1;" ::"r"(sb + XN_S + 2 * pos16(k)), "r"(pk) : "memory");
                }
            }
        }
        TL(1);
    } else if (warp == EW0 + 2) {
        if (lane < 24) __stcg(&g_slot3[blockIdx.x * (STR3 * 8) + lane], make_uint4(SENT, SENT, SENT, SENT));
        if (c < 12) {
#pragma unroll
            for (int i = 0; i < 6; i++) __stcg(&g_slot5[(r * 12 + c) * (STR5 * 8) + 32 * i + lane], make_uint4(SENT, SENT, SENT, SENT));
        }
    }
    __syncwarp();
    asm volatile("barrier.cluster.arrive.relaxed.aligned;" ::: "memory");
    if (warp >= PW0) asm volatile("bar.arrive 2, %0;" ::"n"(NTHREADS) : "memory");
    else asm volatile("bar.sync 2, %0;" ::"n"(NTHREADS) : "memory");
    if (warp == 0) TL(19);

    if (warp >= PW0) {
        asm volatile("bar.sync 3, %0;" ::"n"(NPROD * 32) : "memory");
        const int sV = nK, sO = 2 * nK, s1 = sO + nO, s2 = s1 + 6, total = s2 + 6;
        const int tauK = r < 4 ? T_K / 11 : T_K / 10, tauV = r < 4 ? T_V / 11 : T_V / 10, tauO = r < 4 ? T_O / 5 : T_O / 6;
        for (int s = warp - PW0; s < total; s += NPROD) {
            const char* src; uint32_t dst, dp, sp, bytes; int bar, ebar = -1, when;
            if (s < sO) {
                const bool isv = s >= sV;
                const int j = s - (isv ? sV : 0);
                src = (isv ? gv : gk) + kvbase + (size_t)j * KV_STEP;
                dst = isv ? (j < 8 ? V_OFF + j * KV_STAGE : (j - 8) * KV_STAGE) : K_OFF + j * KV_STAGE;
                dp = KV_GRP; sp = 1024; bytes = 1024; bar = (isv ? B_V : B_K) + j;
                if (isv && j >= 8) ebar = B_WQDONE;
                when = isv ? T_K + j * tauV : j * tauK;
            } else if (s < s1) {
                const int j = s - sO;
                src = gwo + (size_t)(256 * c + 8 * (u0 + j)) * 1152; dst = WO_OFF + j * WR_STAGE;
                dp = WR_PITCH; sp = 1152; bytes = 1152; bar = B_WO + j; ebar = j < 2 ? B_WQDONE : B_KDONE;
                when = T_K + T_V + j * tauO;
            } else if (s < s2) {
                const int j = s - s1;
                src = gw1 + (size_t)(96 * r + 16 * j) * (FF * 2) + 576 * c; dst = W1_OFF + j * W1_STAGE;
                dp = W1_PITCH; sp = FF * 2; bytes = 576; bar = B_W1 + j; ebar = B_KDONE;
                when = T_K + T_V + T_O + j * TAU_1;
            } else {
                const int j = s - s2;
                src = gw2 + (size_t)(288 * c + 48 * r + 8 * j) * 1152; dst = W2_OFF + j * WR_STAGE;
                dp = WR_PITCH; sp = 1152; bytes = 1152; bar = B_W2 + j; ebar = B_VDONE;
                when = T_K + T_V + T_O + 6 * TAU_1 + (j < 2 ? j * TAU_2A : 2 * TAU_2A + (j - 2) * TAU_2B);
            }
            if (ebar >= 0) { mbar_wait(bars + 8 * ebar); asm volatile("fence.proxy.async.shared::cta;" ::: "memory"); }
            const int dep = s - WIN_CAP;
            if (dep >= 0) mbar_wait(bars + 8 * (dep < sV ? B_K + dep : dep < sO ? B_V + dep - sV : dep < s1 ? B_WO + dep - sO : B_W1 + dep - s1));
            const unsigned t_go = t_start + PACE_T0 - SKEW * c + when;
            for (int it = 0; it < 100000; it++) {
                unsigned now; asm volatile("mov.u32 %0, %%globaltimer_lo;" : "=r"(now));
                if ((int)(now - t_go) >= 0) break;
            }
            if (elect()) {
                const int nh = bytes == 576 ? 2 : 1;
#pragma unroll 1
                for (int h = 0; h < nh; h++) issue8(sb + dst + 8 * h * dp, dp, src + (size_t)(8 * h) * sp, sp, bytes, bars + 8 * bar, pol);
            }
            __syncwarp();
        }
        asm volatile("barrier.cluster.wait.aligned;" ::: "memory");
    } else if (warp >= EW0) {
        const int e = warp - EW0, et = tid - EW0 * 32;
        if (e == 2) {
            asm volatile("fence.acq_rel.gpu;" ::: "memory");
            __syncwarp();
            TL(2);
            if (lane == 0) {
                unsigned v;
                asm volatile("atom.relaxed.gpu.global.add.u32 %0, [%1], 1;" : "=r"(v) : "l"(G_ARRIVE) : "memory");
                const unsigned target = (v / NCTA + 1) * NCTA;
                for (unsigned it = 0; (int)(++v - target) < 0; it++) {
                    asm volatile("ld.acquire.gpu.global.u32 %0, [%1];" : "=r"(v) : "l"(G_ARRIVE) : "memory");
                    v--;
                    if (it > 0x400000u) __trap();
                }
                mbar_arrive(bars + 8 * B_INIT);
            }
            __syncwarp();
            TL(22);
        }
        asm volatile("barrier.cluster.wait.aligned;" ::: "memory");
        if (e < 2) {
            mbar_wait(bars + 8 * B_X1);
            float a0 = 0.f, a1 = 0.f, a2 = 0.f, a3 = 0.f;
#pragma unroll
            for (int s = 0; s < CS; s++) {
                const uint4 v = lds128(sb + X1R + s * 1024 + et * 16);
                a0 += __uint_as_float(v.x); a1 += __uint_as_float(v.y); a2 += __uint_as_float(v.z); a3 += __uint_as_float(v.w);
            }
            const int w = et >> 2;
            sts64(sb + Q_S + ((w >> 3) * 4 + (et & 3)) * 80 + (w & 7) * 8, pack2(a0, a2), pack2(a1, a3));
            __syncwarp();
            if (lane == 0) mbar_arrive(bars + 8 * B_Q);
            if (e == 0) TL(3);
            mbar_wait(bars + 8 * B_X2);
            if (et < 8 * nO) {
                const int head = (u0 + (et >> 3)) >> 4;
                float m[CS], l[CS], o[CS];
#pragma unroll
                for (int s = 0; s < CS; s++) {
                    const uint2 v = lds64(sb + X2S + s * 16 + head * 8);
                    m[s] = __uint_as_float(v.x); l[s] = __uint_as_float(v.y);
                    o[s] = ldsf(sb + X2R + (s * 48 + et) * 4);
                }
                float M = m[0];
#pragma unroll
                for (int s = 1; s < CS; s++) M = fmaxf(M, m[s]);
                float L = 0.f, acc = 0.f;
#pragma unroll
                for (int s = 0; s < CS; s++) { const float ws = ex2((m[s] - M) * LOG2E); L += ws * l[s]; acc += ws * o[s]; }
                sts16(sb + O_S + 2 * et, f2bf(__fdividef(acc, L)));
            }
            __syncwarp();
            if (lane == 0) mbar_arrive(bars + 8 * B_O);
            if (e == 0) TL(4);
        }
        {
            uint32_t* p3 = pin(reinterpret_cast<uint32_t*>(g_slot3) + r * NCL * (STR3 * 32) + et);
            uint32_t* pw = pin(p3 + c * (STR3 * 32));
            const float xres = ldsf(sb + X_S + 4 * et);
            const int lc = et;
            const uint32_t hdst = pin(sb + H_S + 2 * pos16(lc));
            mbar_wait(bars + 8 * B_INIT);
            mbar_wait(bars + 8 * B_X3);
            {
                float a[CS];
#pragma unroll
                for (int s = 0; s < CS; s++) a[s] = ldsf(sb + X3R + (s * 96 + et) * 4);
                publish<RED3>(pw, ((a[0] + a[1]) + (a[2] + a[3])) + (a[4] + a[5]));
            }
            if (e == 0) TL(5);
            const float attn = gather_sum<NCL>(p3, STR3 * 32, ATOM_TH);
            TL(6 + 14 * (e > 0) + (e > 1));
            const float h = bfr(xres + bfr(attn));
            sts16(hdst, (uint16_t)(__float_as_uint(h) >> 16));
            stsf(sb + HF_S + 4 * lc, h);
            asm volatile("bar.arrive 4, %0;" ::"n"(NMMA * 32 + 96) : "memory");
            __syncwarp();
            if (lane == 0) mbar_arrive(bars + 8 * B_H);
            TL(53 + e);
            const float k0 = __shfl_sync(0xFFFFFFFFu, h, 0);
            float s = h - k0, q = s * s;
#pragma unroll
            for (int m = 16; m; m >>= 1) { s += shx(s, m); q += shx(q, m); }
            if (lane < CS) st_async4(mapa(sb + X4S + (r * 3 + e) * 16, lane), k0, s, q, 0.f, mapa(bars + 8 * B_X4S, lane));
        }
        {
            mbar_wait(bars + 8 * B_X4S);
            if (e == 0) TL(26);
            const float kc = ldsf(sb + X4S);
            const uint4 st = lds128(sb + X4S + (lane < 18 ? lane : 0) * 16);
            const float dk = __uint_as_float(st.x) - kc, gs = __uint_as_float(st.y);
            float s = lane < 18 ? gs + 32.0f * dk : 0.f;
            float q = lane < 18 ? __uint_as_float(st.z) + dk * (2.0f * gs + 32.0f * dk) : 0.f;
#pragma unroll
            for (int m = 16; m; m >>= 1) { s += shx(s, m); q += shx(q, m); }
            const float dm = s * (1.0f / DM);
            const float var = fmaxf(q * (1.0f / DM) - dm * dm, 0.f);
            const float mb = bfr(kc + dm), rsd = __fdividef(1.0f, bfr(sqrt_fast(bfr(bfr(var) + 1e-5f))));
            mbar_wait(bars + 8 * B_X4);
            if (e == 0) TL(7);
            const int f = 16 * e + (lane >> 1);
            float s1 = 0.f, s2 = 0.f;
#pragma unroll
            for (int i = 0; i < 3; i++) {
                const uint2 v = lds64(sb + X4R + ((3 * (lane & 1) + i) * 48 + f) * 8);
                s1 += __uint_as_float(v.x); s2 += __uint_as_float(v.y);
            }
            float pre = s1 - mb * s2;
            pre = bfr((pre + shx(pre, 1)) * rsd);
            const float act = __fdividef(pre, 1.0f + ex2(-pre * LOG2E));
            if (!(lane & 1)) sts16(sb + H1_S + 2 * f, f2bf(act));
            asm volatile("bar.arrive 5, %0;" ::"n"(NMMA * 32 + 96) : "memory");
            TL(56 + e);
        }
        if (e == 0 && c < 12) {
            TL(8);
            const uint4* p5 = pin(g_slot5 + (r * 12 + c) * (STR5 * 8) + lane);
            const int lc = 8 * c + 4 * (lane & 1) + 2 * (lane >> 4) + ((lane >> 3) & 1);
            uint16_t* pout = pin(reinterpret_cast<uint16_t*>(gout) + 96 * r + lc);
            mbar_wait(bars + 8 * B_H);
            const float hres = ldsf(sb + HF_S + 4 * lc);
            uint4 v[6];
#pragma unroll
            for (int k = 0; k < 6; k++) v[k] = ldg_rlx128(p5 + k * 32);
            float a0, a1, a2, a3;
            for (unsigned it = 0;; it++) {
#define SUM6(f) (((__uint_as_float(v[0].f) + __uint_as_float(v[1].f)) + (__uint_as_float(v[2].f) + __uint_as_float(v[3].f))) + (__uint_as_float(v[4].f) + __uint_as_float(v[5].f)))
                a0 = SUM6(x); a1 = SUM6(y); a2 = SUM6(z); a3 = SUM6(w);
#undef SUM6
                const float chk = (a0 + a1) + (a2 + a3);
                if (!__any_sync(0xFFFFFFFFu, chk != chk)) break;
                bool miss = false;
#pragma unroll
                for (int k = 0; k < 6; k++) { const bool m = has_sent(v[k]); miss |= m; ldg_rlx128_if(v[k], p5 + k * 32, m); }
                if (!__any_sync(0xFFFFFFFFu, miss)) break;
                if (it > 0x400000u) __trap();
            }
            TL(9);
            const bool h16 = lane & 16, h8 = lane & 8;
            const float b0 = (h16 ? a2 : a0) + shx(h16 ? a0 : a2, 16), b1 = (h16 ? a3 : a1) + shx(h16 ? a1 : a3, 16);
            float y = (h8 ? b1 : b0) + shx(h8 ? b0 : b1, 8);
            y += shx(y, 4); y += shx(y, 2);
            if (!(lane & 6)) *pout = f2bf(hres + bfr(y));
            TL(10);
        }
    } else {
        const int w = warp;
        if (w < 16) {
            uint2 b[6];
#pragma unroll
            for (int ks = 0; ks < 6; ks++) b[ks] = lds64(sb + XN_S + (ks * 4 + t) * 8);
            float acc[2][4] = {};
            const uint32_t ab = sb + WQ_OFF + ((lane & 7) + 8 * (lane >> 4)) * WQ_PITCH + (2 * w + ((lane >> 3) & 1)) * 16;
#pragma unroll
            for (int ks = 0; ks < 6; ks++) {
                mbar_wait(bars + 8 * (B_WQ + 2 * ks)); mbar_wait(bars + 8 * (B_WQ + 2 * ks + 1));
                uint32_t a[4]; ldsm4t(a, ab + ks * WQ_STAGE);
                mma16(acc[ks & 1], a, b[ks].x, b[ks].y);
            }
            const float c0 = acc[0][0] + acc[1][0], c2 = acc[0][2] + acc[1][2];
            if (w == 0) TL(11);
            asm volatile("barrier.cluster.wait.aligned;" ::: "memory");
            const uint32_t da = sb + X1R + r * 1024 + (w * 8 + g) * 8;
            st_async2(mapa(da, t), c0, c2, mapa(bars + 8 * B_X1, t));
            if (t < 2) st_async2(mapa(da, t + 4), c0, c2, mapa(bars + 8 * B_X1, t + 4));
            if (lane == 0) mbar_arrive(bars + 8 * B_WQDONE);
        } else {
            asm volatile("barrier.cluster.wait.aligned;" ::: "memory");
        }
        const int head = t & 1, half = t >> 1;
        float sc[2];
        {
            mbar_wait(bars + 8 * B_Q);
            uint32_t qb[16];
#pragma unroll
            for (int j = 0; j < 4; j++) {
                const uint4 v = lds128(sb + Q_S + ((g & 1) * 4 + t) * 80 + j * 16);
                qb[4 * j] = v.x; qb[4 * j + 1] = v.y; qb[4 * j + 2] = v.z; qb[4 * j + 3] = v.w;
            }
#pragma unroll
            for (int it = 0; it < 2; it++) {
                const int tau = w + NMMA * it;
                sc[it] = -INFINITY;
                if (tau < 2 * nK) {
                    mbar_wait(bars + 8 * (B_K + (tau >> 1)));
                    const uint32_t ab = sb + K_OFF + (tau >> 1) * KV_STAGE + (lane & 7) * KV_GRP + ((tau & 1) * 2 + ((lane >> 3) & 1)) * 256 + (lane >> 4) * 16;
                    float acc[2][4] = {};
#pragma unroll
                    for (int ks = 0; ks < 8; ks++) {
                        uint32_t a[4]; ldsm4(a, ab + ks * 32);
                        mma16(acc[ks & 1], a, qb[2 * ks], qb[2 * ks + 1]);
                    }
                    const float raw = pick4(acc[0][0] + acc[1][0], acc[0][1] + acc[1][1], acc[0][2] + acc[1][2], acc[0][3] + acc[1][3], t);
                    sc[it] = bfr(bfr(raw) * 0.08838834764831845f);
                }
            }
        }
        float M = fmaxf(sc[0], sc[1]);
#pragma unroll
        for (int m = 2; m <= 16; m <<= 1) M = fmaxf(M, shx(M, m));
        if (lane < 2) stsf(sb + WMAX + (2 * w + lane) * 4, M);
        if (lane == 0) mbar_arrive(bars + 8 * B_KDONE);
        if (w == 0) TL(12);
        bar_mma();
        M = ldsf(sb + WMAX + lane * 4);
        if (lane < 4) M = fmaxf(M, ldsf(sb + WMAX + (32 + lane) * 4));
#pragma unroll
        for (int m = 2; m <= 16; m <<= 1) M = fmaxf(M, shx(M, m));
        {
            float ls = 0.f;
#pragma unroll
            for (int it = 0; it < 2; it++) {
                const int tau = w + NMMA * it;
                if (tau < 2 * nK) {
                    const float pb = bfr(ex2((sc[it] - M) * LOG2E));
                    ls += pb;
                    sts16(sb + P_S + head * 704 + (tau * 16 + (g >> 1) * 4 + half * 2 + (g & 1)) * 2, (uint16_t)(__float_as_uint(pb) >> 16));
                }
            }
#pragma unroll
            for (int m = 2; m <= 16; m <<= 1) ls += shx(ls, m);
            if (lane < 2) stsf(sb + WSUM + (2 * w + lane) * 4, ls);
        }
        bar_mma();
        if (w == 8) {
            float L = ldsf(sb + WSUM + lane * 4);
            if (lane < 4) L += ldsf(sb + WSUM + (32 + lane) * 4);
#pragma unroll
            for (int m = 2; m <= 16; m <<= 1) L += shx(L, m);
            const float Mo = shx(M, 1), Lo = shx(L, 1);
            if (lane < CS) st_async4(mapa(sb + X2S + r * 16, lane), head ? Mo : M, head ? Lo : L, head ? M : Mo, head ? L : Lo, mapa(bars + 8 * B_X2, lane));
            TL(13);
        }
        if (w < 8) {
            float acc[2][4] = {};
            const uint32_t ao = sb + (lane & 7) * KV_GRP + (lane >> 4) * 256 + (2 * w + ((lane >> 3) & 1)) * 16;
            const uint32_t pb = sb + P_S + (g & 1) * 704 + t * 8;
#pragma unroll
            for (int j = 0; j < 11; j++) {
                if (j < nK) {
                    const uint2 b0 = lds64(pb + j * 64), b1 = lds64(pb + j * 64 + 32);
                    mbar_wait(bars + 8 * (B_V + j));
                    const uint32_t ab = ao + (j < 8 ? V_OFF + j * KV_STAGE : (j - 8) * KV_STAGE);
                    uint32_t a0[4], a1[4];
                    ldsm4t(a0, ab); ldsm4t(a1, ab + 512);
                    mma16(acc[0], a0, b0.x, b0.y);
                    mma16(acc[1], a1, b1.x, b1.y);
                    if (j == 6 && lane == 0) mbar_arrive(bars + 8 * B_VDONE);
                }
            }
            const float val = pick4(acc[0][0] + acc[1][0], acc[0][1] + acc[1][1], acc[0][2] + acc[1][2], acc[0][3] + acc[1][3], t);
            const int u = 16 * head + 2 * w + half;
            const int dest = u < 20 ? u / 5 : (u < 26 ? 4 : 5);
            const int ud = u - (dest < 5 ? 5 * dest : 26);
            st_async1(mapa(sb + X2R + (r * 48 + ud * 8 + g) * 4, dest), val, mapa(bars + 8 * B_X2, dest));
            if (w == 0) TL(14);
        }
        const int rd = w / 3, jd = w - 3 * rd;
        const uint32_t wro = pin(sb + (lane & 7) * WR_PITCH + (lane >> 4) * WR_STAGE + (4 * w + ((lane >> 3) & 1)) * 16);
        {
            const uint32_t da = mapa(sb + X3R + (r * 96 + 32 * jd + 8 * t + g) * 4, rd), db = mapa(bars + 8 * B_X3, rd);
            mbar_wait(bars + 8 * B_O);
            uint32_t b[6];
#pragma unroll
            for (int u = 0; u < 6; u++) b[u] = lds32(sb + O_S + (8 * u + 2 * t) * 2);
            if (nO == 5) b[5] = 0;
            float accA[4] = {}, accB[4] = {};
#pragma unroll
            for (int u = 0; u < 6; u += 2) {
                mbar_wait(bars + 8 * (B_WO + u));
                uint32_t ad = wro + WO_OFF + u * WR_STAGE, a0[4], a1[4];
                if (u + 1 < nO) mbar_wait(bars + 8 * (B_WO + u + 1));
                else ad -= (lane >> 4) * WR_STAGE;
                ldsm4t(a0, ad); ldsm4t(a1, ad + 32);
                mma16(accA, a0, b[u], b[u + 1]);
                mma16(accB, a1, b[u], b[u + 1]);
            }
            st_async1(da, pick4(accA[0], accA[2], accB[0], accB[2], t), db);
            if (w == 0) TL(15);
            if (w == 17) TL(23);
        }
        {
            uint32_t a[6][4];
            const uint32_t ab = sb + W1_OFF + ((lane & 7) + 8 * (lane >> 4)) * W1_PITCH + (2 * w + ((lane >> 3) & 1)) * 16;
#pragma unroll
            for (int ks = 0; ks < 6; ks++) { mbar_wait(bars + 8 * (B_W1 + ks)); ldsm4t(a[ks], ab + ks * W1_STAGE); }
            const uint32_t hb = sb + ((g & 1) ? ONES_S : H_S) + t * 8;
            const uint32_t da = pin(mapa(sb + X4R + (r * 48 + 16 * jd + 8 * (t & 1) + g) * 8, rd)), db = pin(mapa(bars + 8 * B_X4, rd));
            if (w == 0) TL(16);
            asm volatile("bar.sync 4, %0;" ::"n"(NMMA * 32 + 96) : "memory");
            if (w == 0) TL(28);
            float acc[2][4] = {};
#pragma unroll
            for (int ks = 0; ks < 6; ks++) {
                const uint2 b = lds64(hb + ks * 32);
                mma16(acc[ks & 1], a[ks], b.x, b.y);
            }
            if (t < 2) {
                const float s1 = t ? acc[0][2] + acc[1][2] : acc[0][0] + acc[1][0];
                const float s2 = t ? acc[0][3] + acc[1][3] : acc[0][1] + acc[1][1];
                st_async2(da, s1, s2, db);
            }
            __syncwarp();
            if (w == 0) TL(24);
            if (w == 17) TL(25);
        }
        {
            float* pw = pin(reinterpret_cast<float*>(g_slot5) + (4 * w + t) * (STR5 * 32) + blockIdx.x * 8 + g);
            uint32_t a[4][4];
#pragma unroll
            for (int u = 0; u < 4; u += 2) {
                mbar_wait(bars + 8 * (B_W2 + u)); mbar_wait(bars + 8 * (B_W2 + u + 1));
                ldsm4t(a[u], wro + W2_OFF + u * WR_STAGE); ldsm4t(a[u + 1], wro + W2_OFF + u * WR_STAGE + 32);
            }
            if (w == 0) TL(27);
            asm volatile("bar.sync 5, %0;" ::"n"(NMMA * 32 + 96) : "memory");
            if (w == 0) TL(29);
            uint32_t b[6];
#pragma unroll
            for (int u = 0; u < 6; u++) b[u] = lds32(sb + H1_S + (8 * u + 2 * t) * 2);
            float accA[4] = {}, accB[4] = {};
            mma16(accA, a[0], b[0], b[1]); mma16(accB, a[1], b[0], b[1]);
            mma16(accA, a[2], b[2], b[3]); mma16(accB, a[3], b[2], b[3]);
            mbar_wait(bars + 8 * (B_W2 + 4)); mbar_wait(bars + 8 * (B_W2 + 5));
            if (w == 0) TL(17);
            ldsm4t(a[0], wro + W2_OFF + 4 * WR_STAGE); ldsm4t(a[1], wro + W2_OFF + 4 * WR_STAGE + 32);
            mma16(accA, a[0], b[4], b[5]); mma16(accB, a[1], b[4], b[5]);
            publish<RED5>(pw, pick4(accA[0], accA[2], accB[0], accB[2], t));
            TL(32 + w);
        }
    }
}

}

extern "C" void kernel_launch(void* const* d_in, const int* in_sizes, int n_in, void* d_out, int out_size) {
    (void)in_sizes; (void)n_in; (void)out_size;
    static bool configured = false;
    if (!configured) {
        cudaFuncSetAttribute(fused_decode_kernel, cudaFuncAttributeMaxDynamicSharedMemorySize, SMEM_BYTES);
        configured = true;
    }
    fused_decode_kernel<<<NCTA, NTHREADS, SMEM_BYTES>>>(
        (const __nv_bfloat16*)d_in[0], (const char*)d_in[1], (const char*)d_in[2], (const char*)d_in[3],
        (const char*)d_in[4], (const char*)d_in[6], (const char*)d_in[7], (__nv_bfloat16*)d_out);
}
```

```cpp
#include <cuda_runtime.h>
#include <cuda_bf16.h>
#include <stdint.h>

namespace {

constexpr int DM = 576, SK = 8192, WIN = 2048, FF = 4608;
constexpr int CS = 6, NCL = 16, NCTA = CS * NCL;
constexpr int NMMA = 18;
constexpr int EW0 = 18;
constexpr int PW0 = 21, NPROD = 4;
constexpr int NTHREADS = (PW0 + NPROD) * 32;

constexpr int PACE_T0 = 740, T_K = 2615, T_V = 2720, T_O = 1660, TAU_1 = 272, TAU_2A = 320, TAU_2B = 260, T_G = 0, T_G2 = 0, WIN_CAP = 8, CAP_O = 8, CAP_1 = 6, CAP_2 = 6, ATOM_TH = 5;
#define RED3 1
#define RED5 1
#define CONST_POL 0
#define GUARD 1
#define NAMED_H 1
#define USE_EVICT_FIRST 1

constexpr int WQ_PITCH = 544, KV_GRP = 1056, KV_STAGE = 8 * KV_GRP, WR_PITCH = 1184, WR_STAGE = 8 * WR_PITCH;
constexpr int W1_PITCH = 608, W1_STAGE = 16 * W1_PITCH, WQ_STAGE = 16 * WQ_PITCH;
constexpr int WQ_OFF = 0;
constexpr int K_OFF = 96 * WQ_PITCH;
constexpr int V_OFF = K_OFF + 11 * KV_STAGE;
constexpr int RING_END = V_OFF + 8 * KV_STAGE;
constexpr int WO_OFF = 3 * KV_STAGE;
constexpr int W1_OFF = WO_OFF + 6 * WR_STAGE;
constexpr int W2_OFF = W1_OFF + 6 * W1_STAGE;
static_assert(W2_OFF + 6 * WR_STAGE <= V_OFF + 7 * KV_STAGE, "w2 must only overlap V stages 0..6");
static_assert(WO_OFF + 2 * WR_STAGE <= K_OFF && W1_OFF + 6 * W1_STAGE <= V_OFF, "wo / w1 placement");
constexpr int X1R = RING_END;
constexpr int X2R = X1R + 6144;
constexpr int X2S = X2R + 1152;
constexpr int X3R = X2S + 96;
constexpr int X4R = X3R + 2304;
constexpr int X4S = X4R + 2304;
constexpr int Q_S = X4S + 288;
constexpr int XN_S = Q_S + 1280;
constexpr int P_S = XN_S + 192;
constexpr int WMAX = P_S + 1408;
constexpr int WSUM = WMAX + 160;
constexpr int O_S = WSUM + 160;
constexpr int H_S = O_S + 96;
constexpr int HF_S = H_S + 192;
constexpr int H1_S = HF_S + 384;
constexpr int ZERO_S = H1_S + 96;
constexpr int BARS = ZERO_S + 192;
constexpr int B_WQ = 0, B_K = 12, B_V = 23, B_WO = 34, B_W1 = 40, B_W2 = 46;
constexpr int B_WQDONE = 52, B_KDONE = 53, B_VDONE = 54;
constexpr int B_X1 = 55, B_X2 = 56, B_X3 = 57, B_X4 = 58, B_X4S = 59;
constexpr int B_Q = 60, B_O = 61, B_H = 62, B_H1 = 63, B_INIT = 64;
constexpr int NBAR = 65;
constexpr int SMEM_BYTES = BARS + NBAR * 8;
static_assert(BARS % 8 == 0 && X2S % 16 == 0 && Q_S % 16 == 0 && X4R % 16 == 0 && X1R % 16 == 0, "align");
static_assert(SMEM_BYTES <= 232448, "smem");

constexpr uint32_t SENT = 0xFFFFFFFFu;

constexpr int NOWN = 72;
constexpr int STR3 = 3, STR5 = 24;
__device__ __align__(256) uint4 g_slot3[CS * NCL * STR3 * 8];
__device__ __align__(256) uint4 g_slot5[NOWN * STR5 * 8];
__device__ __align__(256) unsigned g_arrive;
#define G_ARRIVE (&g_arrive)

#define TL(i) do { } while (0)

__device__ __forceinline__ void mbar_init(uint32_t b, uint32_t c) { asm volatile("mbarrier.init.shared::cta.b64 [%0], %1;" ::"r"(b), "r"(c) : "memory"); }
__device__ __forceinline__ void mbar_expect(uint32_t b, uint32_t bytes) { asm volatile("mbarrier.arrive.expect_tx.shared::cta.b64 _, [%0], %1;" ::"r"(b), "r"(bytes) : "memory"); }
__device__ __forceinline__ void mbar_arrive(uint32_t b) { asm volatile("mbarrier.arrive.shared::cta.b64 _, [%0];" ::"r"(b) : "memory"); }
__device__ __forceinline__ void mbar_wait(uint32_t b) {
    asm volatile("{\n.reg .pred p;\n.reg .u32 n;\nmov.u32 n, 0;\n"
                 "W_LOOP:\nmbarrier.try_wait.parity.shared::cta.b64 p, [%0], 0;\n@p bra W_DONE;\n"
                 "add.u32 n, n, 1;\nsetp.lt.u32 p, n, 0x400000;\n@p bra W_LOOP;\ntrap;\nW_DONE:\n}" ::"r"(b) : "memory");
}
__device__ __forceinline__ bool elect() { uint32_t p; asm volatile("{.reg .pred P; elect.sync _|P, 0xffffffff; selp.u32 %0,1,0,P;}" : "=r"(p)); return p; }
__device__ __forceinline__ float ex2(float x) { float y; asm("ex2.approx.ftz.f32 %0, %1;" : "=f"(y) : "f"(x)); return y; }
__device__ __forceinline__ float sqrt_fast(float x) { float y; asm("sqrt.approx.f32 %0, %1;" : "=f"(y) : "f"(x)); return y; }
__device__ __forceinline__ void bulk_g2s(uint32_t dst, const void* src, uint32_t bytes, uint32_t bar, uint64_t pol) {
    asm volatile("cp.async.bulk.shared::cluster.global.mbarrier::complete_tx::bytes.L2::cache_hint [%0], [%1], %2, [%3], %4;" ::"r"(dst), "l"(src), "r"(bytes), "r"(bar), "l"(pol) : "memory");
}
__device__ __forceinline__ uint32_t mapa(uint32_t a, uint32_t rank) { uint32_t r; asm("mapa.shared::cluster.u32 %0, %1, %2;" : "=r"(r) : "r"(a), "r"(rank)); return r; }
__device__ __forceinline__ void st_async1(uint32_t a, float v, uint32_t bar) { asm volatile("st.async.shared::cluster.mbarrier::complete_tx::bytes.b32 [%0], %1, [%2];" ::"r"(a), "r"(__float_as_uint(v)), "r"(bar) : "memory"); }
__device__ __forceinline__ void st_async2(uint32_t a, float x, float y, uint32_t bar) { asm volatile("st.async.shared::cluster.mbarrier::complete_tx::bytes.v2.b32 [%0], {%1,%2}, [%3];" ::"r"(a), "r"(__float_as_uint(x)), "r"(__float_as_uint(y)), "r"(bar) : "memory"); }
__device__ __forceinline__ void st_async4(uint32_t a, float x, float y, float z, float w, uint32_t bar) { asm volatile("st.async.shared::cluster.mbarrier::complete_tx::bytes.v4.b32 [%0], {%1,%2,%3,%4}, [%5];" ::"r"(a), "r"(__float_as_uint(x)), "r"(__float_as_uint(y)), "r"(__float_as_uint(z)), "r"(__float_as_uint(w)), "r"(bar) : "memory"); }
__device__ __forceinline__ void ldsm4(uint32_t (&r)[4], uint32_t a) { asm volatile("ldmatrix.sync.aligned.m8n8.x4.shared.b16 {%0,%1,%2,%3}, [%4];" : "=r"(r[0]), "=r"(r[1]), "=r"(r[2]), "=r"(r[3]) : "r"(a) : "memory"); }
__device__ __forceinline__ void ldsm4t(uint32_t (&r)[4], uint32_t a) { asm volatile("ldmatrix.sync.aligned.m8n8.x4.trans.shared.b16 {%0,%1,%2,%3}, [%4];" : "=r"(r[0]), "=r"(r[1]), "=r"(r[2]), "=r"(r[3]) : "r"(a) : "memory"); }
__device__ __forceinline__ void mma16(float (&c)[4], const uint32_t (&a)[4], uint32_t b0, uint32_t b1) {
    asm volatile("mma.sync.aligned.m16n8k16.row.col.f32.bf16.bf16.f32 {%0,%1,%2,%3}, {%4,%5,%6,%7}, {%8,%9}, {%0,%1,%2,%3};"
                 : "+f"(c[0]), "+f"(c[1]), "+f"(c[2]), "+f"(c[3]) : "r"(a[0]), "r"(a[1]), "r"(a[2]), "r"(a[3]), "r"(b0), "r"(b1));
}
__device__ __forceinline__ uint32_t lds32(uint32_t a) { uint32_t v; asm volatile("ld.shared.b32 %0, [%1];" : "=r"(v) : "r"(a) : "memory"); return v; }
__device__ __forceinline__ float ldsf(uint32_t a) { return __uint_as_float(lds32(a)); }
__device__ __forceinline__ uint2 lds64(uint32_t a) { uint2 v; asm volatile("ld.shared.v2.b32 {%0,%1}, [%2];" : "=r"(v.x), "=r"(v.y) : "r"(a) : "memory"); return v; }
__device__ __forceinline__ uint4 lds128(uint32_t a) { uint4 v; asm volatile("ld.shared.v4.b32 {%0,%1,%2,%3}, [%4];" : "=r"(v.x), "=r"(v.y), "=r"(v.z), "=r"(v.w) : "r"(a) : "memory"); return v; }
__device__ __forceinline__ void sts16(uint32_t a, uint16_t v) { asm volatile("st.shared.b16 [%0], %1;" ::"r"(a), "h"(v) : "memory"); }
__device__ __forceinline__ void stsf(uint32_t a, float v) { asm volatile("st.shared.f32 [%0], %1;" ::"r"(a), "f"(v) : "memory"); }
__device__ __forceinline__ void sts64(uint32_t a, uint32_t x, uint32_t y) { asm volatile("st.shared.v2.b32 [%0], {%1,%2};" ::"r"(a), "r"(x), "r"(y) : "memory"); }
__device__ __forceinline__ uint4 ldg_rlx128(const void* p) { uint4 v; asm volatile("ld.relaxed.gpu.global.v4.b32 {%0,%1,%2,%3}, [%4];" : "=r"(v.x), "=r"(v.y), "=r"(v.z), "=r"(v.w) : "l"(p) : "memory"); return v; }
template <int RED>
__device__ __forceinline__ void publish(void* p, float v) {
    uint32_t u = __float_as_uint(v);
    u = (u == SENT) ? 0x7FFFFFFFu : u;
    if (RED) asm volatile("red.relaxed.gpu.global.and.b32 [%0], %1;" ::"l"(p), "r"(u) : "memory");
    else asm volatile("st.relaxed.gpu.global.b32 [%0], %1;" ::"l"(p), "r"(u) : "memory");
}
__device__ __forceinline__ uint32_t pack2(float lo, float hi) { uint32_t d; asm("cvt.rn.bf16x2.f32 %0, %1, %2;" : "=r"(d) : "f"(hi), "f"(lo)); return d; }
__device__ __forceinline__ uint16_t f2bf(float v) { return (uint16_t)pack2(v, 0.f); }
__device__ __forceinline__ float bfr(float v) { return __uint_as_float(pack2(0.f, v)); }
template <typename T> __device__ __forceinline__ T* pin(T* p) { asm volatile("" : "+l"(p)); return p; }
__device__ __forceinline__ uint32_t pin(uint32_t a) { asm volatile("" : "+r"(a)); return a; }
__device__ __forceinline__ float bflo(uint32_t u) { return __uint_as_float(u << 16); }
__device__ __forceinline__ float bfhi(uint32_t u) { return __uint_as_float(u & 0xFFFF0000u); }
__device__ __forceinline__ float shx(float v, int m) { return __shfl_xor_sync(0xFFFFFFFFu, v, m); }
__device__ __forceinline__ float pick4(float a, float b, float c, float d, int t) { float x = (t & 1) ? b : a, y = (t & 1) ? d : c; return (t & 2) ? y : x; }
__device__ __forceinline__ void bar_mma() { asm volatile("bar.sync 1, %0;" ::"n"(NMMA * 32) : "memory"); }
__device__ __forceinline__ void issue8(uint32_t dst, uint32_t dpitch, const char* src, uint32_t spitch, uint32_t bytes, uint32_t bar, uint64_t pol) {
#pragma unroll
    for (int i = 0; i < 8; i++) bulk_g2s(dst + i * dpitch, src + (size_t)i * spitch, bytes, bar, pol);
}
__device__ __forceinline__ bool has_sent(const uint4& v) { return v.x == SENT || v.y == SENT || v.z == SENT || v.w == SENT; }
__device__ __forceinline__ void ldg_rlx128_if(uint4& v, const void* p, bool pred) {
    asm volatile("{.reg .pred q; setp.ne.u32 q, %5, 0; @q ld.relaxed.gpu.global.v4.b32 {%0,%1,%2,%3}, [%4];}"
                 : "+r"(v.x), "+r"(v.y), "+r"(v.z), "+r"(v.w) : "l"(p), "r"((uint32_t)pred) : "memory");
}
__device__ __forceinline__ uint32_t atom_read(uint32_t* p) { uint32_t v; asm volatile("atom.relaxed.gpu.global.or.b32 %0, [%1], 0;" : "=r"(v) : "l"(p) : "memory"); return v; }
__device__ __forceinline__ uint32_t ld_read(const uint32_t* p) { uint32_t v; asm volatile("ld.relaxed.gpu.global.b32 %0, [%1];" : "=r"(v) : "l"(p) : "memory"); return v; }
__device__ __forceinline__ void ld_read_if(uint32_t& v, const uint32_t* p) { asm volatile("{.reg .pred q; setp.eq.u32 q, %0, 0xFFFFFFFF; @q ld.relaxed.gpu.global.b32 %0, [%1];}" : "+r"(v) : "l"(p) : "memory"); }
template <int N>
__device__ __forceinline__ float gather_sum(uint32_t* p, int stride, int atom_th) {
    uint32_t v[N];
#pragma unroll
    for (int k = 0; k < N; k++) v[k] = ld_read(p + k * stride);
    for (unsigned it = 0;; it++) {
        float a[N / 4];
#pragma unroll
        for (int k = 0; k < N / 4; k++) a[k] = (__uint_as_float(v[4 * k]) + __uint_as_float(v[4 * k + 1])) + (__uint_as_float(v[4 * k + 2]) + __uint_as_float(v[4 * k + 3]));
        float y = (a[0] + a[1]) + (a[2] + a[3]);
        if (N == 24) y += a[N / 4 - 2] + a[N / 4 - 1];
        if (!__any_sync(0xFFFFFFFFu, y != y)) return y;
        uint32_t m = 0;
#pragma unroll
        for (int k = 0; k < N; k++) m |= (v[k] == SENT ? 1u : 0u) << k;
        m = __reduce_or_sync(0xFFFFFFFFu, m);
        if (m == 0) return y;
        if (__popc(m) <= atom_th) {
#pragma unroll
            for (int k = 0; k < N; k++) if (m >> k & 1) v[k] = atom_read(p + k * stride);
        } else {
#pragma unroll
            for (int k = 0; k < N; k++) ld_read_if(v[k], p + k * stride);
        }
        if (it > 0x400000u) __trap();
    }
}
__device__ __forceinline__ int pos16(int k) { return (k & ~15) + ((k & 7) >> 1) * 4 + ((k >> 3) & 1) * 2 + (k & 1); }

constexpr float LOG2E = 1.4426950408889634f;

__global__ void __cluster_dims__(CS, 1, 1) __launch_bounds__(NTHREADS, 1)
fused_decode_kernel(const __nv_bfloat16* __restrict__ gx, const char* __restrict__ gk, const char* __restrict__ gv,
                    const char* __restrict__ gwq, const char* __restrict__ gwo, const char* __restrict__ gw1,
                    const char* __restrict__ gw2, __nv_bfloat16* __restrict__ gout) {
    extern __shared__ __align__(128) unsigned char smem_raw[];
    const char* const wq0 = gwq;
    const uint32_t sb = pin((uint32_t)__cvta_generic_to_shared(smem_raw));
    const uint32_t bars = sb + BARS;
    const int tid = threadIdx.x, lane = tid & 31;
    const int c = blockIdx.y, r = blockIdx.x;
    const int cta = c * CS + r;
    uint64_t pol = 0;
    asm volatile("createpolicy.fractional.L2::evict_first.b64 %0, 1.0;" : "=l"(pol));
    if (__builtin_expect(tid < 12 * 32, 1)) {
        if (elect()) {
            const int w8 = (tid >> 5) * 8;
            const uint32_t b = bars + B_WQ * 8 + w8;
            mbar_init(b, 1);
            issue8(sb + WQ_OFF + w8 * WQ_PITCH, WQ_PITCH, wq0 + (size_t)(96 * r + w8) * 8192 + 512 * c, 8192, 512, b, pol);
            mbar_expect(b, 4096);
        }
    }
    const int warp = __shfl_sync(0xFFFFFFFFu, tid >> 5, 0);
    const int nK = r < 4 ? 11 : 10;
    const int nO = r < 4 ? 5 : 6;
    const int u0 = r < 5 ? 5 * r : 26;
    const int g = lane >> 2, t = lane & 3;
    const size_t kvbase = ((size_t)c * SK + (SK - WIN) + 32 * r) * 256;
    constexpr int KV_STEP = CS * 8192;
    unsigned t_start;
    asm volatile("mov.u32 %0, %%globaltimer_lo;" : "=r"(t_start));
    if (warp < 12) {
    } else if (warp >= PW0) {
        if (elect()) {
            const int p = warp - PW0;
#pragma unroll
            for (int i = 0; i < 10; i++) {
                const uint32_t b = bars + 8 * (B_K + 4 * i + p);
                mbar_init(b, 1); mbar_expect(b, 4 * i + p < 22 ? 8192 : 9216);
            }
            if (p < 3) mbar_init(bars + 8 * (B_WQDONE + p), p == 0 ? 16 : p == 1 ? NMMA : 8);
        }
    } else if (warp == 16) {
        if (lane < 24) sts64(sb + ZERO_S + lane * 8, 0u, 0u);
    } else if (warp == 17) {
        if (elect()) {
            mbar_init(bars + 8 * B_X1, 1); mbar_init(bars + 8 * B_X2, 1); mbar_init(bars + 8 * B_X3, 1); mbar_init(bars + 8 * B_X4, 1); mbar_init(bars + 8 * B_X4S, 1);
            mbar_expect(bars + 8 * B_X1, CS * 1024); mbar_expect(bars + 8 * B_X2, CS * (nO * 32 + 16));
            mbar_expect(bars + 8 * B_X3, CS * 384); mbar_expect(bars + 8 * B_X4, CS * 384); mbar_expect(bars + 8 * B_X4S, 18 * 16);
            mbar_init(bars + 8 * B_Q, 2); mbar_init(bars + 8 * B_O, 2);
            mbar_init(bars + 8 * B_H, 3); mbar_init(bars + 8 * B_H1, 3); mbar_init(bars + 8 * B_INIT, 1);
            asm volatile("fence.mbarrier_init.release.cluster;" ::: "memory");
        }
    } else if (warp == EW0) {
        const uint4* px = reinterpret_cast<const uint4*>(gx);
        const uint4 xv0 = __ldg(px + lane), xv1 = __ldg(px + 32 + lane);
        const uint4 xv2 = lane < 8 ? __ldg(px + 64 + lane) : make_uint4(0, 0, 0, 0);
        const uint32_t w[12] = {xv0.x, xv0.y, xv0.z, xv0.w, xv1.x, xv1.y, xv1.z, xv1.w, xv2.x, xv2.y, xv2.z, xv2.w};
        float s = 0.f;
#pragma unroll
        for (int i = 0; i < 12; i++) s += bflo(w[i]) + bfhi(w[i]);
#pragma unroll
        for (int m = 16; m; m >>= 1) s += shx(s, m);
        const float mean = s * (1.0f / DM);
        float q = 0.f;
#pragma unroll
        for (int i = 0; i < 12; i++) {
            const float a = bflo(w[i]) - mean, b = bfhi(w[i]) - mean;
            if (i < 8 || lane < 8) q += a * a + b * b;
        }
#pragma unroll
        for (int m = 16; m; m >>= 1) q += shx(q, m);
        const float mb = bfr(mean), sd = bfr(sqrt_fast(bfr(bfr(q * (1.0f / DM)) + 1e-5f)));
#pragma unroll
        for (int ch = 0; ch < 3; ch++) {
            const int lc = lane + 32 * ch - 12 * r;
            if (lc >= 0 && lc < 12) {
#pragma unroll
                for (int i = 0; i < 4; i++) {
                    const float a = bflo(w[4 * ch + i]), b = bfhi(w[4 * ch + i]);
                    const int k = 8 * lc + 2 * i;
                    const uint32_t pk = pack2(__fdividef(bfr(a - mb), sd), __fdividef(bfr(b - mb), sd));
                    asm volatile("st.shared.b32 [%0], %1;" ::"r"(sb + XN_S + 2 * pos16(k)), "r"(pk) : "memory");
                }
            }
        }
        TL(1);
    }
    unsigned arrived = 0;
    if (warp == EW0 + 2) {
        asm volatile("barrier.cluster.arrive.relaxed.aligned;" ::: "memory");
        asm volatile("bar.arrive 2, %0;" ::"n"(NTHREADS) : "memory");
        if (lane < 24) __stcg(&g_slot3[cta * (STR3 * 8) + lane], make_uint4(SENT, SENT, SENT, SENT));
        if (c < 12) {
#pragma unroll
            for (int i = 0; i < 6; i++) __stcg(&g_slot5[(r * 12 + c) * (STR5 * 8) + 32 * i + lane], make_uint4(SENT, SENT, SENT, SENT));
        }
        asm volatile("fence.acq_rel.gpu;" ::: "memory");
        __syncwarp();
        TL(2);
        if (lane == 0) asm volatile("atom.relaxed.gpu.global.add.u32 %0, [%1], 1;" : "=r"(arrived) : "l"(G_ARRIVE) : "memory");
    } else {
        __syncwarp();
        asm volatile("barrier.cluster.arrive.relaxed.aligned;" ::: "memory");
        if (warp >= PW0) asm volatile("bar.arrive 2, %0;" ::"n"(NTHREADS) : "memory");
        else asm volatile("bar.sync 2, %0;" ::"n"(NTHREADS) : "memory");
    }
    if (warp == 0) TL(19);

    if (warp >= PW0) {
        asm volatile("bar.sync 3, %0;" ::"n"(NPROD * 32) : "memory");
        const int sV = nK, sO = 2 * nK, s1 = sO + nO, s2 = s1 + 6, total = s2 + 6;
        const int tauK = r < 4 ? T_K / 11 : T_K / 10, tauV = r < 4 ? T_V / 11 : T_V / 10, tauO = r < 4 ? T_O / 5 : T_O / 6;
        for (int s = warp - PW0; s < total; s += NPROD) {
            const char* src; uint32_t dst, dp, sp, bytes; int bar, ebar = -1, when;
            if (s < sO) {
                const bool isv = s >= sV;
                const int j = s - (isv ? sV : 0);
                src = (isv ? gv : gk) + kvbase + (size_t)j * KV_STEP;
                dst = isv ? (j < 8 ? V_OFF + j * KV_STAGE : (j - 8) * KV_STAGE) : K_OFF + j * KV_STAGE;
                dp = KV_GRP; sp = 1024; bytes = 1024; bar = (isv ? B_V : B_K) + j;
                if (isv && j >= 8) ebar = B_WQDONE;
                when = isv ? T_K + j * tauV : j * tauK;
            } else if (s < s1) {
                const int j = s - sO;
                src = gwo + (size_t)(256 * c + 8 * (u0 + j)) * 1152; dst = WO_OFF + j * WR_STAGE;
                dp = WR_PITCH; sp = 1152; bytes = 1152; bar = B_WO + j; ebar = j < 2 ? B_WQDONE : B_KDONE;
                when = T_K + T_V + j * tauO;
            } else if (s < s2) {
                const int j = s - s1;
                src = gw1 + (size_t)(96 * r + 16 * j) * (FF * 2) + 576 * c; dst = W1_OFF + j * W1_STAGE;
                dp = W1_PITCH; sp = FF * 2; bytes = 576; bar = B_W1 + j; ebar = B_KDONE;
                when = T_K + T_V + T_O + T_G + j * TAU_1 + (j >= 3 ? T_G2 : 0);
            } else {
                const int j = s - s2;
                src = gw2 + (size_t)(288 * c + 48 * r + 8 * j) * 1152; dst = W2_OFF + j * WR_STAGE;
                dp = WR_PITCH; sp = 1152; bytes = 1152; bar = B_W2 + j; ebar = B_VDONE;
                when = T_K + T_V + T_O + T_G + T_G2 + 6 * TAU_1 + (j < 2 ? j * TAU_2A : 2 * TAU_2A + (j - 2) * TAU_2B);
            }
            if (ebar >= 0) { mbar_wait(bars + 8 * ebar); asm volatile("fence.proxy.async.shared::cta;" ::: "memory"); }
            const int dep = s - (s < sO ? WIN_CAP : s < s1 ? CAP_O : s < s2 ? CAP_1 : CAP_2);
            if (dep >= 0) mbar_wait(bars + 8 * (dep < sV ? B_K + dep : dep < sO ? B_V + dep - sV : dep < s1 ? B_WO + dep - sO : B_W1 + dep - s1));
            const unsigned t_go = t_start + PACE_T0 + when;
            for (int it = 0; it < 100000; it++) {
                unsigned now; asm volatile("mov.u32 %0, %%globaltimer_lo;" : "=r"(now));
                if ((int)(now - t_go) >= 0) break;
            }
            if (elect()) {
                const int nh = bytes == 576 ? 2 : 1;
#pragma unroll 1
                for (int h = 0; h < nh; h++) issue8(sb + dst + 8 * h * dp, dp, src + (size_t)(8 * h) * sp, sp, bytes, bars + 8 * bar, pol);
            }
            __syncwarp();
        }
        asm volatile("barrier.cluster.wait.aligned;" ::: "memory");
    } else if (warp >= EW0) {
        const int e = warp - EW0, et = tid - EW0 * 32;
        asm volatile("barrier.cluster.wait.aligned;" ::: "memory");
        if (e == 2) {
            if (lane == 0) {
                const unsigned target = (arrived / NCTA + 1) * NCTA;
                for (unsigned it = 0; (int)(++arrived - target) < 0; it++) {
                    asm volatile("ld.acquire.gpu.global.u32 %0, [%1];" : "=r"(arrived) : "l"(G_ARRIVE) : "memory");
                    arrived--;
                    if (it > 0x400000u) __trap();
                }
                mbar_arrive(bars + 8 * B_INIT);
            }
            __syncwarp();
            TL(22);
        }
        if (e < 2) {
            mbar_wait(bars + 8 * B_X1);
            float a0 = 0.f, a1 = 0.f, a2 = 0.f, a3 = 0.f;
#pragma unroll
            for (int s = 0; s < CS; s++) {
                const uint4 v = lds128(sb + X1R + s * 1024 + et * 16);
                a0 += __uint_as_float(v.x); a1 += __uint_as_float(v.y); a2 += __uint_as_float(v.z); a3 += __uint_as_float(v.w);
            }
            const int w = et >> 2;
            const uint32_t qa = sb + Q_S + ((w >> 3) * 4 + (et & 3)) * 80 + (w & 7) * 8, q0 = pack2(a0, a2), q1 = pack2(a1, a3);
            sts64(qa, q0, q1); sts64(qa + 640, q1, q0);
            __syncwarp();
            if (lane == 0) mbar_arrive(bars + 8 * B_Q);
            if (e == 0) TL(3);
            mbar_wait(bars + 8 * B_X2);
            if (et < 8 * nO) {
                const int head = (u0 + (et >> 3)) >> 4;
                float m[CS], l[CS], o[CS];
#pragma unroll
                for (int s = 0; s < CS; s++) {
                    const uint2 v = lds64(sb + X2S + s * 16 + head * 8);
                    m[s] = __uint_as_float(v.x); l[s] = __uint_as_float(v.y);
                    o[s] = ldsf(sb + X2R + (s * 48 + et) * 4);
                }
                float M = m[0];
#pragma unroll
                for (int s = 1; s < CS; s++) M = fmaxf(M, m[s]);
                float L = 0.f, acc = 0.f;
#pragma unroll
                for (int s = 0; s < CS; s++) { const float ws = ex2((m[s] - M) * LOG2E); L += ws * l[s]; acc += ws * o[s]; }
                sts16(sb + O_S + 2 * et, f2bf(__fdividef(acc, L)));
            }
            __syncwarp();
            if (lane == 0) mbar_arrive(bars + 8 * B_O);
            if (e == 0) TL(4);
        }
        {
            uint32_t* p3 = pin(reinterpret_cast<uint32_t*>(g_slot3) + r * NCL * (STR3 * 32) + et);
            uint32_t* pw = pin(p3 + c * (STR3 * 32));
            const float xres = __bfloat162float(__ldg(gx + 96 * r + et));
            const int lc = et;
            const uint32_t hdst = pin(sb + H_S + 2 * pos16(lc));
            mbar_wait(bars + 8 * B_INIT);
            mbar_wait(bars + 8 * B_X3);
            {
                float a[CS];
#pragma unroll
                for (int s = 0; s < CS; s++) a[s] = ldsf(sb + X3R + (s * 96 + et) * 4);
                publish<RED3>(pw, ((a[0] + a[1]) + (a[2] + a[3])) + (a[4] + a[5]));
            }
            if (e == 0) TL(5);
            const float attn = gather_sum<NCL>(p3, STR3 * 32, ATOM_TH);
            TL(6 + 14 * (e > 0) + (e > 1));
            const float h = bfr(xres + bfr(attn));
            sts16(hdst, (uint16_t)(__float_as_uint(h) >> 16));
            stsf(sb + HF_S + 4 * lc, h);
            asm volatile("bar.arrive 4, %0;" ::"n"(NMMA * 32 + 96) : "memory");
            __syncwarp();
            if (lane == 0) mbar_arrive(bars + 8 * B_H);
            TL(53 + e);
            const float k0 = __shfl_sync(0xFFFFFFFFu, h, 0);
            float s = h - k0, q = s * s;
#pragma unroll
            for (int m = 16; m; m >>= 1) { s += shx(s, m); q += shx(q, m); }
            if (lane < CS) st_async4(mapa(sb + X4S + (r * 3 + e) * 16, lane), k0, s, q, 0.f, mapa(bars + 8 * B_X4S, lane));
        }
        {
            mbar_wait(bars + 8 * B_X4S);
            if (e == 0) TL(26);
            const float kc = ldsf(sb + X4S);
            const uint4 st = lds128(sb + X4S + (lane < 18 ? lane : 0) * 16);
            const float dk = __uint_as_float(st.x) - kc, gs = __uint_as_float(st.y);
            float s = lane < 18 ? gs + 32.0f * dk : 0.f;
            float q = lane < 18 ? __uint_as_float(st.z) + dk * (2.0f * gs + 32.0f * dk) : 0.f;
#pragma unroll
            for (int m = 16; m; m >>= 1) { s += shx(s, m); q += shx(q, m); }
            const float dm = s * (1.0f / DM);
            const float var = fmaxf(q * (1.0f / DM) - dm * dm, 0.f);
            const float mb = bfr(kc + dm), rsd = __fdividef(1.0f, bfr(sqrt_fast(bfr(bfr(var) + 1e-5f))));
            mbar_wait(bars + 8 * B_X4);
            if (e == 0) TL(7);
            const int f = 16 * e + (lane >> 1);
            float s1 = 0.f, s2 = 0.f;
#pragma unroll
            for (int i = 0; i < 3; i++) {
                const uint2 v = lds64(sb + X4R + ((3 * (lane & 1) + i) * 48 + f) * 8);
                s1 += __uint_as_float(v.x); s2 += __uint_as_float(v.y);
            }
            float pre = s1 - mb * s2;
            pre = bfr((pre + shx(pre, 1)) * rsd);
            const float act = __fdividef(pre, 1.0f + ex2(-pre * LOG2E));
            if (!(lane & 1)) sts16(sb + H1_S + 2 * f, f2bf(act));
            asm volatile("bar.arrive 5, %0;" ::"n"(NMMA * 32 + 96) : "memory");
            TL(56 + e);
        }
        if (e == 0 && c < 12) {
            TL(8);
            const uint4* p5 = pin(g_slot5 + (r * 12 + c) * (STR5 * 8) + lane);
            const int lc = 8 * c + 4 * (lane & 1) + 2 * (lane >> 4) + ((lane >> 3) & 1);
            uint16_t* pout = pin(reinterpret_cast<uint16_t*>(gout) + 96 * r + lc);
            mbar_wait(bars + 8 * B_H);
            const float hres = ldsf(sb + HF_S + 4 * lc);
            uint4 v[6];
#pragma unroll
            for (int k = 0; k < 6; k++) v[k] = ldg_rlx128(p5 + k * 32);
            float a0, a1, a2, a3;
            for (unsigned it = 0;; it++) {
#define SUM6(f) (((__uint_as_float(v[0].f) + __uint_as_float(v[1].f)) + (__uint_as_float(v[2].f) + __uint_as_float(v[3].f))) + (__uint_as_float(v[4].f) + __uint_as_float(v[5].f)))
                a0 = SUM6(x); a1 = SUM6(y); a2 = SUM6(z); a3 = SUM6(w);
#undef SUM6
                const float chk = (a0 + a1) + (a2 + a3);
                if (!__any_sync(0xFFFFFFFFu, chk != chk)) break;
                bool miss = false;
#pragma unroll
                for (int k = 0; k < 6; k++) { const bool m = has_sent(v[k]); miss |= m; ldg_rlx128_if(v[k], p5 + k * 32, m); }
                if (!__any_sync(0xFFFFFFFFu, miss)) break;
                if (it > 0x400000u) __trap();
            }
            TL(9);
            const bool h16 = lane & 16, h8 = lane & 8;
            const float b0 = (h16 ? a2 : a0) + shx(h16 ? a0 : a2, 16), b1 = (h16 ? a3 : a1) + shx(h16 ? a1 : a3, 16);
            float y = (h8 ? b1 : b0) + shx(h8 ? b0 : b1, 8);
            y += shx(y, 4); y += shx(y, 2);
            if (!(lane & 6)) *pout = f2bf(hres + bfr(y));
            TL(10);
        }
    } else {
        const int w = warp;
        const int cx = ((lane >> 3) ^ (lane >> 2)) & 1;
        const bool act = (t >> 1) == (g & 1);
        if (w < 16) {
            uint2 b[6];
#pragma unroll
            for (int ks = 0; ks < 6; ks++) b[ks] = lds64(sb + (act ? XN_S : ZERO_S) + (ks * 4 + t) * 8);
            float acc[2][4] = {};
            const uint32_t ab = sb + WQ_OFF + ((lane & 7) + 8 * (lane >> 4)) * WQ_PITCH + (2 * w + cx) * 16;
#pragma unroll
            for (int ks = 0; ks < 6; ks++) {
                mbar_wait(bars + 8 * (B_WQ + 2 * ks)); mbar_wait(bars + 8 * (B_WQ + 2 * ks + 1));
                uint32_t a[4]; ldsm4t(a, ab + ks * WQ_STAGE);
                mma16(acc[ks & 1], a, b[ks].x, b[ks].y);
            }
            const float c0 = (acc[0][0] + acc[1][0]) + (acc[0][3] + acc[1][3]), c2 = (acc[0][2] + acc[1][2]) + (acc[0][1] + acc[1][1]);
            if (w == 0) TL(11);
            asm volatile("barrier.cluster.wait.aligned;" ::: "memory");
            const uint32_t da = sb + X1R + r * 1024 + (w * 8 + g) * 8;
            st_async2(mapa(da, t), c0, c2, mapa(bars + 8 * B_X1, t));
            if (t < 2) st_async2(mapa(da, t + 4), c0, c2, mapa(bars + 8 * B_X1, t + 4));
            if (lane == 0) mbar_arrive(bars + 8 * B_WQDONE);
        } else {
            asm volatile("barrier.cluster.wait.aligned;" ::: "memory");
        }
        const int head = t & 1, half = t >> 1;
        float sc[2];
        {
            mbar_wait(bars + 8 * B_Q);
            uint32_t qb[16];
#pragma unroll
            for (int j = 0; j < 4; j++) {
                const uint4 v = lds128(sb + Q_S + (((g >> 1) & 1) * 8 + (g & 1) * 4 + t) * 80 + j * 16);
                qb[4 * j] = v.x; qb[4 * j + 1] = v.y; qb[4 * j + 2] = v.z; qb[4 * j + 3] = v.w;
            }
#pragma unroll
            for (int it = 0; it < 2; it++) {
                const int tau = w + NMMA * it;
                sc[it] = -INFINITY;
                if (tau < 2 * nK) {
                    mbar_wait(bars + 8 * (B_K + (tau >> 1)));
                    const uint32_t ab = sb + K_OFF + (tau >> 1) * KV_STAGE + (lane & 7) * KV_GRP + ((tau & 1) * 2 + ((lane >> 3) & 1)) * 256 + (((lane >> 4) ^ (lane >> 2)) & 1) * 16;
                    float acc[2][4] = {};
#pragma unroll
                    for (int ks = 0; ks < 8; ks++) {
                        uint32_t a[4]; ldsm4(a, ab + ks * 32);
                        mma16(acc[ks & 1], a, qb[2 * ks], qb[2 * ks + 1]);
                    }
                    const float x0 = half ? acc[0][2] + acc[1][2] : acc[0][0] + acc[1][0], x1 = half ? acc[0][3] + acc[1][3] : acc[0][1] + acc[1][1];
                    const float other = shx(head ? x0 : x1, 1);
                    const float raw = head == (g >> 2) ? (head ? x1 : x0) : other;
                    sc[it] = bfr(bfr(raw) * 0.08838834764831845f);
                }
            }
        }
        float M = fmaxf(sc[0], sc[1]);
#pragma unroll
        for (int m = 2; m <= 16; m <<= 1) M = fmaxf(M, shx(M, m));
        if (lane < 2) stsf(sb + WMAX + (2 * w + lane) * 4, M);
        if (lane == 0) mbar_arrive(bars + 8 * B_KDONE);
        if (w == 0) TL(12);
        bar_mma();
        M = ldsf(sb + WMAX + lane * 4);
        if (lane < 4) M = fmaxf(M, ldsf(sb + WMAX + (32 + lane) * 4));
#pragma unroll
        for (int m = 2; m <= 16; m <<= 1) M = fmaxf(M, shx(M, m));
        {
            float ls = 0.f;
#pragma unroll
            for (int it = 0; it < 2; it++) {
                const int tau = w + NMMA * it;
                if (tau < 2 * nK) {
                    const float pb = bfr(ex2((sc[it] - M) * LOG2E));
                    ls += pb;
                    sts16(sb + P_S + head * 704 + (tau * 16 + (g >> 1) * 4 + half * 2 + (g & 1)) * 2, (uint16_t)(__float_as_uint(pb) >> 16));
                }
            }
#pragma unroll
            for (int m = 2; m <= 16; m <<= 1) ls += shx(ls, m);
            if (lane < 2) stsf(sb + WSUM + (2 * w + lane) * 4, ls);
        }
        bar_mma();
        if (w == 8) {
            float L = ldsf(sb + WSUM + lane * 4);
            if (lane < 4) L += ldsf(sb + WSUM + (32 + lane) * 4);
#pragma unroll
            for (int m = 2; m <= 16; m <<= 1) L += shx(L, m);
            const float Mo = shx(M, 1), Lo = shx(L, 1);
            if (lane < CS) st_async4(mapa(sb + X2S + r * 16, lane), head ? Mo : M, head ? Lo : L, head ? M : Mo, head ? L : Lo, mapa(bars + 8 * B_X2, lane));
            TL(13);
        }
        if (w < 8) {
            float acc[2][4] = {};
            const uint32_t ao = sb + (lane & 7) * KV_GRP + (lane >> 4) * 256 + (2 * w + cx) * 16;
            const uint32_t pb = sb + P_S + (g & 1) * 704 + t * 8;
            const uint32_t pm = (t >> 1) == ((g >> 1) & 1) ? 0xFFFFFFFFu : 0u;
#pragma unroll
            for (int j = 0; j < 11; j++) {
                if (j < nK) {
                    const uint2 b0 = lds64(pb + j * 64), b1 = lds64(pb + j * 64 + 32);
                    mbar_wait(bars + 8 * (B_V + j));
                    const uint32_t ab = ao + (j < 8 ? V_OFF + j * KV_STAGE : (j - 8) * KV_STAGE);
                    uint32_t a0[4], a1[4];
                    ldsm4t(a0, ab); ldsm4t(a1, ab + 512);
                    mma16(acc[0], a0, b0.x & pm, b0.y & pm);
                    mma16(acc[1], a1, b1.x & pm, b1.y & pm);
                    if (j == 6 && lane == 0) mbar_arrive(bars + 8 * B_VDONE);
                }
            }
            const float own = half ? acc[0][1] + acc[1][1] : acc[0][0] + acc[1][0], snd = half ? acc[0][3] + acc[1][3] : acc[0][2] + acc[1][2];
            const float val = own + shx(snd, 1);
            const int u = 16 * half + 2 * w + head;
            const int dest = u < 20 ? u / 5 : (u < 26 ? 4 : 5);
            const int ud = u - (dest < 5 ? 5 * dest : 26);
            st_async1(mapa(sb + X2R + (r * 48 + ud * 8 + g) * 4, dest), val, mapa(bars + 8 * B_X2, dest));
            if (w == 0) TL(14);
        }
        const int rd = w / 3, jd = w - 3 * rd;
        const uint32_t wro = pin(sb + (lane & 7) * WR_PITCH + (lane >> 4) * WR_STAGE + (4 * w + cx) * 16);
        {
            const uint32_t da = mapa(sb + X3R + (r * 96 + 32 * jd + 8 * t + g) * 4, rd), db = mapa(bars + 8 * B_X3, rd);
            mbar_wait(bars + 8 * B_O);
            uint32_t b[6];
#pragma unroll
            for (int u = 0; u < 6; u++) b[u] = lds32(sb + (act ? O_S : ZERO_S) + (8 * u + 2 * t) * 2);
            if (nO == 5) b[5] = 0;
            float accA[4] = {}, accB[4] = {};
#pragma unroll
            for (int u = 0; u < 6; u += 2) {
                mbar_wait(bars + 8 * (B_WO + u));
                uint32_t ad = wro + WO_OFF + u * WR_STAGE, a0[4], a1[4];
                if (u + 1 < nO) mbar_wait(bars + 8 * (B_WO + u + 1));
                else ad -= (lane >> 4) * WR_STAGE;
                ldsm4t(a0, ad); ldsm4t(a1, ad + 32);
                mma16(accA, a0, b[u], b[u + 1]);
                mma16(accB, a1, b[u], b[u + 1]);
            }
            st_async1(da, pick4(accA[0], accA[2], accB[0], accB[2], t) + pick4(accA[3], accA[1], accB[3], accB[1], t), db);
            if (w == 0) TL(15);
        }
        {
            uint32_t a[6][4];
            float cs[4] = {};
            const uint32_t ab = sb + W1_OFF + ((lane & 7) + 8 * (lane >> 4)) * W1_PITCH + (2 * w + cx) * 16;
            const uint32_t ones = act ? 0x3F803F80u : 0u;
#pragma unroll
            for (int ks = 0; ks < 6; ks++) { mbar_wait(bars + 8 * (B_W1 + ks)); ldsm4t(a[ks], ab + ks * W1_STAGE); mma16(cs, a[ks], ones, ones); }
            const float s2 = (t & 1) ? cs[2] + cs[1] : cs[0] + cs[3];
            const uint32_t hb = pin(sb + (act ? H_S : ZERO_S) + t * 8);
            const uint32_t da = pin(mapa(sb + X4R + (r * 48 + 16 * jd + 8 * (t & 1) + g) * 8, rd)), db = pin(mapa(bars + 8 * B_X4, rd));
            if (w == 0) TL(16);
            asm volatile("bar.sync 4, %0;" ::"n"(NMMA * 32 + 96) : "memory");
            if (w == 0) TL(28);
            float acc[2][4] = {};
#pragma unroll
            for (int ks = 0; ks < 6; ks++) {
                const uint2 b = lds64(hb + ks * 32);
                mma16(acc[ks & 1], a[ks], b.x, b.y);
            }
            if (t < 2) {
                const float s1 = t ? (acc[0][2] + acc[1][2]) + (acc[0][1] + acc[1][1]) : (acc[0][0] + acc[1][0]) + (acc[0][3] + acc[1][3]);
                st_async2(da, s1, s2, db);
            }
            __syncwarp();
            if (w == 0) TL(24);
            if (w == 17) TL(25);
        }
        {
            float* pw = pin(reinterpret_cast<float*>(g_slot5) + (4 * w + t) * (STR5 * 32) + cta * 8 + g);
            const uint32_t hb = pin(sb + (act ? H1_S : ZERO_S) + t * 4);
            uint32_t a[4][4];
#pragma unroll
            for (int u = 0; u < 4; u += 2) {
                mbar_wait(bars + 8 * (B_W2 + u)); mbar_wait(bars + 8 * (B_W2 + u + 1));
                ldsm4t(a[u], wro + W2_OFF + u * WR_STAGE); ldsm4t(a[u + 1], wro + W2_OFF + u * WR_STAGE + 32);
            }
            if (w == 0) TL(27);
            asm volatile("bar.sync 5, %0;" ::"n"(NMMA * 32 + 96) : "memory");
            if (w == 0) TL(29);
            uint32_t b[6];
#pragma unroll
            for (int u = 0; u < 6; u++) b[u] = lds32(hb + 16 * u);
            float accA[4] = {}, accB[4] = {};
            mma16(accA, a[0], b[0], b[1]); mma16(accB, a[1], b[0], b[1]);
            mma16(accA, a[2], b[2], b[3]); mma16(accB, a[3], b[2], b[3]);
            mbar_wait(bars + 8 * (B_W2 + 4)); mbar_wait(bars + 8 * (B_W2 + 5));
            if (w == 0) TL(17);
            ldsm4t(a[0], wro + W2_OFF + 4 * WR_STAGE); ldsm4t(a[1], wro + W2_OFF + 4 * WR_STAGE + 32);
            mma16(accA, a[0], b[4], b[5]); mma16(accB, a[1], b[4], b[5]);
            publish<RED5>(pw, pick4(accA[0], accA[2], accB[0], accB[2], t) + pick4(accA[3], accA[1], accB[3], accB[1], t));
            TL(32 + w);
        }
    }
}

}

extern "C" void kernel_launch(void* const* d_in, const int* in_sizes, int n_in, void* d_out, int out_size) {
    (void)in_sizes; (void)n_in; (void)out_size;
    static bool configured = false;
    if (!configured) {
        cudaFuncSetAttribute(fused_decode_kernel, cudaFuncAttributeMaxDynamicSharedMemorySize, SMEM_BYTES);
        configured = true;
    }
    fused_decode_kernel<<<dim3(CS, NCL), NTHREADS, SMEM_BYTES>>>(
        (const __nv_bfloat16*)d_in[0], (const char*)d_in[1], (const char*)d_in[2], (const char*)d_in[3],
        (const char*)d_in[4], (const char*)d_in[6], (const char*)d_in[7], (__nv_bfloat16*)d_out);
}
```

```cpp
#include <cuda_runtime.h>
#include <cuda_bf16.h>
#include <stdint.h>

namespace {

constexpr int DM = 576, SK = 8192, WIN = 2048, FF = 4608;
constexpr int CS = 6, NCL = 16, NCTA = CS * NCL;
constexpr int NMMA = 18;
constexpr int EW0 = 18;
constexpr int PW0 = 21, NPROD = 4;
constexpr int NTHREADS = (PW0 + NPROD) * 32;

constexpr int PACE_T0 = 740, T_K = 2615, T_V = 2720, T_O = 1660, TAU_1 = 272, TAU_2A = 320, TAU_2B = 260, T_G = 0, T_G2 = 0, WIN_CAP = 8, CAP_O = 8, CAP_1 = 6, CAP_2 = 6, ATOM_TH = 5;
#define RED3 1
#define RED5 1
#define GUARD 1
#define NAMED_H 1
#define USE_EVICT_FIRST 1

constexpr int WQ_PITCH = 544, KV_GRP = 1056, KV_STAGE = 8 * KV_GRP, WR_PITCH = 1184, WR_STAGE = 8 * WR_PITCH;
constexpr int W1_PITCH = 608, W1_STAGE = 16 * W1_PITCH, WQ_STAGE = 16 * WQ_PITCH;
constexpr int WQ_OFF = 0;
constexpr int K_OFF = 96 * WQ_PITCH;
constexpr int V_OFF = K_OFF + 11 * KV_STAGE;
constexpr int RING_END = V_OFF + 8 * KV_STAGE;
constexpr int WO_OFF = 3 * KV_STAGE;
constexpr int W1_OFF = WO_OFF + 6 * WR_STAGE;
constexpr int W2_OFF = W1_OFF + 6 * W1_STAGE;
static_assert(W2_OFF + 6 * WR_STAGE <= V_OFF + 7 * KV_STAGE, "w2 must only overlap V stages 0..6");
static_assert(WO_OFF + 2 * WR_STAGE <= K_OFF && W1_OFF + 6 * W1_STAGE <= V_OFF, "wo / w1 placement");
constexpr int X1R = RING_END;
constexpr int X2R = X1R + 6144;
constexpr int X2S = X2R + 1152;
constexpr int X3R = X2S + 96;
constexpr int X4R = X3R + 2304;
constexpr int X4S = X4R + 2304;
constexpr int Q_S = X4S + 288;
constexpr int XN_S = Q_S + 1280;
constexpr int P_S = XN_S + 192;
constexpr int WMAX = P_S + 1408;
constexpr int WSUM = WMAX + 160;
constexpr int O_S = WSUM + 160;
constexpr int H_S = O_S + 96;
constexpr int HF_S = H_S + 192;
constexpr int H1_S = HF_S + 384;
constexpr int ZERO_S = H1_S + 96;
constexpr int BARS = ZERO_S + 192;
constexpr int B_WQ = 0, B_K = 12, B_V = 23, B_WO = 34, B_W1 = 40, B_W2 = 46;
constexpr int B_WQDONE = 52, B_KDONE = 53, B_VDONE = 54;
constexpr int B_X1 = 55, B_X2 = 56, B_X3 = 57, B_X4 = 58, B_X4S = 59;
constexpr int B_Q = 60, B_O = 61, B_H = 62, B_H1 = 63, B_INIT = 64;
constexpr int NBAR = 65;
constexpr int SMEM_BYTES = BARS + NBAR * 8;
static_assert(BARS % 8 == 0 && X2S % 16 == 0 && Q_S % 16 == 0 && X4R % 16 == 0 && X1R % 16 == 0, "align");
static_assert(SMEM_BYTES <= 232448, "smem");

constexpr uint32_t SENT = 0xFFFFFFFFu;

constexpr int NOWN = 72;
constexpr int STR3 = 3, STR5 = 24;
struct __align__(256) Scratch {
    uint4 slot5[NOWN * STR5 * 8];
    uint4 slot3[CS * NCL * STR3 * 8];
    unsigned arrive;
};
__device__ Scratch g_scratch;
#define g_slot3 (scr->slot3)
#define g_slot5 (scr->slot5)
#define G_ARRIVE (&scr->arrive)

#define TL(i) do { } while (0)

__device__ __forceinline__ void mbar_init(uint32_t b, uint32_t c) { asm volatile("mbarrier.init.shared::cta.b64 [%0], %1;" ::"r"(b), "r"(c) : "memory"); }
__device__ __forceinline__ void mbar_expect(uint32_t b, uint32_t bytes) { asm volatile("mbarrier.arrive.expect_tx.shared::cta.b64 _, [%0], %1;" ::"r"(b), "r"(bytes) : "memory"); }
__device__ __forceinline__ void mbar_arrive(uint32_t b) { asm volatile("mbarrier.arrive.shared::cta.b64 _, [%0];" ::"r"(b) : "memory"); }
__device__ __forceinline__ void mbar_wait(uint32_t b) {
    asm volatile("{\n.reg .pred p;\n.reg .u32 n;\nmov.u32 n, 0;\n"
                 "W_LOOP:\nmbarrier.try_wait.parity.shared::cta.b64 p, [%0], 0;\n@p bra W_DONE;\n"
                 "add.u32 n, n, 1;\nsetp.lt.u32 p, n, 0x400000;\n@p bra W_LOOP;\ntrap;\nW_DONE:\n}" ::"r"(b) : "memory");
}
__device__ __forceinline__ bool elect() { uint32_t p; asm volatile("{.reg .pred P; elect.sync _|P, 0xffffffff; selp.u32 %0,1,0,P;}" : "=r"(p)); return p; }
__device__ __forceinline__ float ex2(float x) { float y; asm("ex2.approx.ftz.f32 %0, %1;" : "=f"(y) : "f"(x)); return y; }
__device__ __forceinline__ float sqrt_fast(float x) { float y; asm("sqrt.approx.f32 %0, %1;" : "=f"(y) : "f"(x)); return y; }
__device__ __forceinline__ void bulk_g2s(uint32_t dst, const void* src, uint32_t bytes, uint32_t bar, uint64_t pol) {
    asm volatile("cp.async.bulk.shared::cluster.global.mbarrier::complete_tx::bytes.L2::cache_hint [%0], [%1], %2, [%3], %4;" ::"r"(dst), "l"(src), "r"(bytes), "r"(bar), "l"(pol) : "memory");
}
__device__ __forceinline__ uint32_t mapa(uint32_t a, uint32_t rank) { uint32_t r; asm("mapa.shared::cluster.u32 %0, %1, %2;" : "=r"(r) : "r"(a), "r"(rank)); return r; }
__device__ __forceinline__ void st_async1(uint32_t a, float v, uint32_t bar) { asm volatile("st.async.shared::cluster.mbarrier::complete_tx::bytes.b32 [%0], %1, [%2];" ::"r"(a), "r"(__float_as_uint(v)), "r"(bar) : "memory"); }
__device__ __forceinline__ void st_async2(uint32_t a, float x, float y, uint32_t bar) { asm volatile("st.async.shared::cluster.mbarrier::complete_tx::bytes.v2.b32 [%0], {%1,%2}, [%3];" ::"r"(a), "r"(__float_as_uint(x)), "r"(__float_as_uint(y)), "r"(bar) : "memory"); }
__device__ __forceinline__ void st_async4(uint32_t a, float x, float y, float z, float w, uint32_t bar) { asm volatile("st.async.shared::cluster.mbarrier::complete_tx::bytes.v4.b32 [%0], {%1,%2,%3,%4}, [%5];" ::"r"(a), "r"(__float_as_uint(x)), "r"(__float_as_uint(y)), "r"(__float_as_uint(z)), "r"(__float_as_uint(w)), "r"(bar) : "memory"); }
__device__ __forceinline__ void ldsm4(uint32_t (&r)[4], uint32_t a) { asm volatile("ldmatrix.sync.aligned.m8n8.x4.shared.b16 {%0,%1,%2,%3}, [%4];" : "=r"(r[0]), "=r"(r[1]), "=r"(r[2]), "=r"(r[3]) : "r"(a) : "memory"); }
__device__ __forceinline__ void ldsm4t(uint32_t (&r)[4], uint32_t a) { asm volatile("ldmatrix.sync.aligned.m8n8.x4.trans.shared.b16 {%0,%1,%2,%3}, [%4];" : "=r"(r[0]), "=r"(r[1]), "=r"(r[2]), "=r"(r[3]) : "r"(a) : "memory"); }
__device__ __forceinline__ void mma16(float (&c)[4], const uint32_t (&a)[4], uint32_t b0, uint32_t b1) {
    asm volatile("mma.sync.aligned.m16n8k16.row.col.f32.bf16.bf16.f32 {%0,%1,%2,%3}, {%4,%5,%6,%7}, {%8,%9}, {%0,%1,%2,%3};"
                 : "+f"(c[0]), "+f"(c[1]), "+f"(c[2]), "+f"(c[3]) : "r"(a[0]), "r"(a[1]), "r"(a[2]), "r"(a[3]), "r"(b0), "r"(b1));
}
__device__ __forceinline__ uint32_t lds32(uint32_t a) { uint32_t v; asm volatile("ld.shared.b32 %0, [%1];" : "=r"(v) : "r"(a) : "memory"); return v; }
__device__ __forceinline__ float ldsf(uint32_t a) { return __uint_as_float(lds32(a)); }
__device__ __forceinline__ uint2 lds64(uint32_t a) { uint2 v; asm volatile("ld.shared.v2.b32 {%0,%1}, [%2];" : "=r"(v.x), "=r"(v.y) : "r"(a) : "memory"); return v; }
__device__ __forceinline__ uint4 lds128(uint32_t a) { uint4 v; asm volatile("ld.shared.v4.b32 {%0,%1,%2,%3}, [%4];" : "=r"(v.x), "=r"(v.y), "=r"(v.z), "=r"(v.w) : "r"(a) : "memory"); return v; }
__device__ __forceinline__ void sts16(uint32_t a, uint16_t v) { asm volatile("st.shared.b16 [%0], %1;" ::"r"(a), "h"(v) : "memory"); }
__device__ __forceinline__ void stsf(uint32_t a, float v) { asm volatile("st.shared.f32 [%0], %1;" ::"r"(a), "f"(v) : "memory"); }
__device__ __forceinline__ void sts64(uint32_t a, uint32_t x, uint32_t y) { asm volatile("st.shared.v2.b32 [%0], {%1,%2};" ::"r"(a), "r"(x), "r"(y) : "memory"); }
__device__ __forceinline__ uint4 ldg_rlx128(const void* p) { uint4 v; asm volatile("ld.relaxed.gpu.global.v4.b32 {%0,%1,%2,%3}, [%4];" : "=r"(v.x), "=r"(v.y), "=r"(v.z), "=r"(v.w) : "l"(p) : "memory"); return v; }
template <int RED>
__device__ __forceinline__ void publish(void* p, float v) {
    uint32_t u = __float_as_uint(v);
    u = (u == SENT) ? 0x7FFFFFFFu : u;
    if (RED) asm volatile("red.relaxed.gpu.global.and.b32 [%0], %1;" ::"l"(p), "r"(u) : "memory");
    else asm volatile("st.relaxed.gpu.global.b32 [%0], %1;" ::"l"(p), "r"(u) : "memory");
}
__device__ __forceinline__ uint32_t pack2(float lo, float hi) { uint32_t d; asm("cvt.rn.bf16x2.f32 %0, %1, %2;" : "=r"(d) : "f"(hi), "f"(lo)); return d; }
__device__ __forceinline__ uint16_t f2bf(float v) { return (uint16_t)pack2(v, 0.f); }
__device__ __forceinline__ float bfr(float v) { return __uint_as_float(pack2(0.f, v)); }
template <typename T> __device__ __forceinline__ T* pin(T* p) { asm volatile("" : "+l"(p)); return p; }
__device__ __forceinline__ uint32_t pin(uint32_t a) { asm volatile("" : "+r"(a)); return a; }
__device__ __forceinline__ float bflo(uint32_t u) { return __uint_as_float(u << 16); }
__device__ __forceinline__ float bfhi(uint32_t u) { return __uint_as_float(u & 0xFFFF0000u); }
__device__ __forceinline__ float shx(float v, int m) { return __shfl_xor_sync(0xFFFFFFFFu, v, m); }
__device__ __forceinline__ float pick4(float a, float b, float c, float d, int t) { float x = (t & 1) ? b : a, y = (t & 1) ? d : c; return (t & 2) ? y : x; }
__device__ __forceinline__ void bar_mma() { asm volatile("bar.sync 1, %0;" ::"n"(NMMA * 32) : "memory"); }
__device__ __forceinline__ void issue8(uint32_t dst, uint32_t dpitch, const char* src, uint32_t spitch, uint32_t bytes, uint32_t bar, uint64_t pol) {
#pragma unroll
    for (int i = 0; i < 8; i++) bulk_g2s(dst + i * dpitch, src + (size_t)i * spitch, bytes, bar, pol);
}
__device__ __forceinline__ bool has_sent(const uint4& v) { return v.x == SENT || v.y == SENT || v.z == SENT || v.w == SENT; }
__device__ __forceinline__ void ldg_rlx128_if(uint4& v, const void* p, bool pred) {
    asm volatile("{.reg .pred q; setp.ne.u32 q, %5, 0; @q ld.relaxed.gpu.global.v4.b32 {%0,%1,%2,%3}, [%4];}"
                 : "+r"(v.x), "+r"(v.y), "+r"(v.z), "+r"(v.w) : "l"(p), "r"((uint32_t)pred) : "memory");
}
__device__ __forceinline__ uint32_t atom_read(uint32_t* p) { uint32_t v; asm volatile("atom.relaxed.gpu.global.or.b32 %0, [%1], 0;" : "=r"(v) : "l"(p) : "memory"); return v; }
__device__ __forceinline__ uint32_t ld_read(const uint32_t* p) { uint32_t v; asm volatile("ld.relaxed.gpu.global.b32 %0, [%1];" : "=r"(v) : "l"(p) : "memory"); return v; }
__device__ __forceinline__ void ld_read_if(uint32_t& v, const uint32_t* p) { asm volatile("{.reg .pred q; setp.eq.u32 q, %0, 0xFFFFFFFF; @q ld.relaxed.gpu.global.b32 %0, [%1];}" : "+r"(v) : "l"(p) : "memory"); }
template <int N>
__device__ __forceinline__ float gather_sum(uint32_t* p, int stride, int atom_th) {
    uint32_t v[N];
#pragma unroll
    for (int k = 0; k < N; k++) v[k] = ld_read(p + k * stride);
    for (unsigned it = 0;; it++) {
        float a[N / 4];
#pragma unroll
        for (int k = 0; k < N / 4; k++) a[k] = (__uint_as_float(v[4 * k]) + __uint_as_float(v[4 * k + 1])) + (__uint_as_float(v[4 * k + 2]) + __uint_as_float(v[4 * k + 3]));
        float y = (a[0] + a[1]) + (a[2] + a[3]);
        if (N == 24) y += a[N / 4 - 2] + a[N / 4 - 1];
        if (!__any_sync(0xFFFFFFFFu, y != y)) return y;
        uint32_t m = 0;
#pragma unroll
        for (int k = 0; k < N; k++) m |= (v[k] == SENT ? 1u : 0u) << k;
        m = __reduce_or_sync(0xFFFFFFFFu, m);
        if (m == 0) return y;
        if (__popc(m) <= atom_th) {
#pragma unroll
            for (int k = 0; k < N; k++) if (m >> k & 1) v[k] = atom_read(p + k * stride);
        } else {
#pragma unroll
            for (int k = 0; k < N; k++) ld_read_if(v[k], p + k * stride);
        }
        if (it > 0x400000u) __trap();
    }
}
__device__ __forceinline__ int pos16(int k) { return (k & ~15) + ((k & 7) >> 1) * 4 + ((k >> 3) & 1) * 2 + (k & 1); }

constexpr float LOG2E = 1.4426950408889634f;

__global__ void __cluster_dims__(CS, 1, 1) __launch_bounds__(NTHREADS, 1)
fused_decode_kernel(const __nv_bfloat16* __restrict__ gx, const char* __restrict__ gk, const char* __restrict__ gv,
                    const char* __restrict__ gwq, const char* __restrict__ gwo, const char* __restrict__ gw1,
                    const char* __restrict__ gw2, __nv_bfloat16* __restrict__ gout, Scratch* __restrict__ scr
) {
    extern __shared__ __align__(128) unsigned char smem_raw[];
    const char* const wq0 = gwq;
    const uint32_t sb = pin((uint32_t)__cvta_generic_to_shared(smem_raw));
    const uint32_t bars = sb + BARS;
    const int tid = threadIdx.x, lane = tid & 31;
    const int c = blockIdx.x / CS, r = blockIdx.x - c * CS;
    uint64_t pol = 0;
    asm volatile("createpolicy.fractional.L2::evict_first.b64 %0, 1.0;" : "=l"(pol));
    if (__builtin_expect(tid < 12 * 32, 1)) {
        if (elect()) {
            const int w8 = (tid >> 5) * 8;
            const uint32_t b = bars + B_WQ * 8 + w8;
            mbar_init(b, 1);
            issue8(sb + WQ_OFF + w8 * WQ_PITCH, WQ_PITCH, wq0 + (size_t)(96 * r + w8) * 8192 + 512 * c, 8192, 512, b, pol);
            mbar_expect(b, 4096);
        }
    }
    const int warp = __shfl_sync(0xFFFFFFFFu, tid >> 5, 0);
    const int nK = r < 4 ? 11 : 10;
    const int nO = r < 4 ? 5 : 6;
    const int u0 = r < 5 ? 5 * r : 26;
    const int g = lane >> 2, t = lane & 3;
    const size_t kvbase = ((size_t)c * SK + (SK - WIN) + 32 * r) * 256;
    constexpr int KV_STEP = CS * 8192;
    unsigned t_start;
    asm volatile("mov.u32 %0, %%globaltimer_lo;" : "=r"(t_start));
    if (warp < 12) {
    } else if (warp >= PW0) {
        if (elect()) {
            const int p = warp - PW0;
#pragma unroll
            for (int i = 0; i < 10; i++) {
                const uint32_t b = bars + 8 * (B_K + 4 * i + p);
                mbar_init(b, 1); mbar_expect(b, 4 * i + p < 22 ? 8192 : 9216);
            }
            if (p < 3) mbar_init(bars + 8 * (B_WQDONE + p), p == 0 ? 16 : p == 1 ? NMMA : 8);
        }
    } else if (warp == 16) {
        if (lane < 24) sts64(sb + ZERO_S + lane * 8, 0u, 0u);
    } else if (warp == 17) {
        if (elect()) {
            mbar_init(bars + 8 * B_X1, 1); mbar_init(bars + 8 * B_X2, 1); mbar_init(bars + 8 * B_X3, 1); mbar_init(bars + 8 * B_X4, 1); mbar_init(bars + 8 * B_X4S, 1);
            mbar_expect(bars + 8 * B_X1, CS * 1024); mbar_expect(bars + 8 * B_X2, CS * (nO * 32 + 16));
            mbar_expect(bars + 8 * B_X3, CS * 384); mbar_expect(bars + 8 * B_X4, CS * 384); mbar_expect(bars + 8 * B_X4S, 18 * 16);
            mbar_init(bars + 8 * B_Q, 2); mbar_init(bars + 8 * B_O, 2);
            mbar_init(bars + 8 * B_H, 3); mbar_init(bars + 8 * B_H1, 3); mbar_init(bars + 8 * B_INIT, 1);
            asm volatile("fence.mbarrier_init.release.cluster;" ::: "memory");
        }
    } else if (warp == EW0) {
        const uint4* px = reinterpret_cast<const uint4*>(gx);
        const uint4 xv0 = __ldg(px + lane), xv1 = __ldg(px + 32 + lane);
        const uint4 xv2 = lane < 8 ? __ldg(px + 64 + lane) : make_uint4(0, 0, 0, 0);
        const uint32_t w[12] = {xv0.x, xv0.y, xv0.z, xv0.w, xv1.x, xv1.y, xv1.z, xv1.w, xv2.x, xv2.y, xv2.z, xv2.w};
        float s = 0.f;
#pragma unroll
        for (int i = 0; i < 12; i++) s += bflo(w[i]) + bfhi(w[i]);
#pragma unroll
        for (int m = 16; m; m >>= 1) s += shx(s, m);
        const float mean = s * (1.0f / DM);
        float q = 0.f;
#pragma unroll
        for (int i = 0; i < 12; i++) {
            const float a = bflo(w[i]) - mean, b = bfhi(w[i]) - mean;
            if (i < 8 || lane < 8) q += a * a + b * b;
        }
#pragma unroll
        for (int m = 16; m; m >>= 1) q += shx(q, m);
        const float mb = bfr(mean), sd = bfr(sqrt_fast(bfr(bfr(q * (1.0f / DM)) + 1e-5f)));
#pragma unroll
        for (int ch = 0; ch < 3; ch++) {
            const int lc = lane + 32 * ch - 12 * r;
            if (lc >= 0 && lc < 12) {
#pragma unroll
                for (int i = 0; i < 4; i++) {
                    const float a = bflo(w[4 * ch + i]), b = bfhi(w[4 * ch + i]);
                    const int k = 8 * lc + 2 * i;
                    const uint32_t pk = pack2(__fdividef(bfr(a - mb), sd), __fdividef(bfr(b - mb), sd));
                    asm volatile("st.shared.b32 [%0], %1;" ::"r"(sb + XN_S + 2 * pos16(k)), "r"(pk) : "memory");
                }
            }
        }
        TL(1);
    }
    unsigned arrived = 0;
    if (warp == EW0 + 2) {
        asm volatile("barrier.cluster.arrive.relaxed.aligned;" ::: "memory");
        asm volatile("bar.arrive 2, %0;" ::"n"(NTHREADS) : "memory");
        if (lane < 24) __stcg(&g_slot3[blockIdx.x * (STR3 * 8) + lane], make_uint4(SENT, SENT, SENT, SENT));
        if (c < 12) {
#pragma unroll
            for (int i = 0; i < 6; i++) __stcg(&g_slot5[(r * 12 + c) * (STR5 * 8) + 32 * i + lane], make_uint4(SENT, SENT, SENT, SENT));
        }
        asm volatile("fence.acq_rel.gpu;" ::: "memory");
        __syncwarp();
        TL(2);
        if (lane == 0) asm volatile("atom.relaxed.gpu.global.add.u32 %0, [%1], 1;" : "=r"(arrived) : "l"(G_ARRIVE) : "memory");
    } else {
        __syncwarp();
        asm volatile("barrier.cluster.arrive.relaxed.aligned;" ::: "memory");
        if (warp >= PW0) asm volatile("bar.arrive 2, %0;" ::"n"(NTHREADS) : "memory");
        else asm volatile("bar.sync 2, %0;" ::"n"(NTHREADS) : "memory");
    }
    if (warp == 0) TL(19);

    if (warp >= PW0) {
        asm volatile("bar.sync 3, %0;" ::"n"(NPROD * 32) : "memory");
        const int sV = nK, sO = 2 * nK, s1 = sO + nO, s2 = s1 + 6, total = s2 + 6;
        const int tauK = r < 4 ? T_K / 11 : T_K / 10, tauV = r < 4 ? T_V / 11 : T_V / 10, tauO = r < 4 ? T_O / 5 : T_O / 6;
        for (int s = warp - PW0; s < total; s += NPROD) {
            const char* src; uint32_t dst, dp, sp, bytes; int bar, ebar = -1, when;
            if (s < sO) {
                const bool isv = s >= sV;
                const int j = s - (isv ? sV : 0);
                src = (isv ? gv : gk) + kvbase + (size_t)j * KV_STEP;
                dst = isv ? (j < 8 ? V_OFF + j * KV_STAGE : (j - 8) * KV_STAGE) : K_OFF + j * KV_STAGE;
                dp = KV_GRP; sp = 1024; bytes = 1024; bar = (isv ? B_V : B_K) + j;
                if (isv && j >= 8) ebar = B_WQDONE;
                when = isv ? T_K + j * tauV : j * tauK;
            } else if (s < s1) {
                const int j = s - sO;
                src = gwo + (size_t)(256 * c + 8 * (u0 + j)) * 1152; dst = WO_OFF + j * WR_STAGE;
                dp = WR_PITCH; sp = 1152; bytes = 1152; bar = B_WO + j; ebar = j < 2 ? B_WQDONE : B_KDONE;
                when = T_K + T_V + j * tauO;
            } else if (s < s2) {
                const int j = s - s1;
                src = gw1 + (size_t)(96 * r + 16 * j) * (FF * 2) + 576 * c; dst = W1_OFF + j * W1_STAGE;
                dp = W1_PITCH; sp = FF * 2; bytes = 576; bar = B_W1 + j; ebar = B_KDONE;
                when = T_K + T_V + T_O + T_G + j * TAU_1 + (j >= 3 ? T_G2 : 0);
            } else {
                const int j = s - s2;
                src = gw2 + (size_t)(288 * c + 48 * r + 8 * j) * 1152; dst = W2_OFF + j * WR_STAGE;
                dp = WR_PITCH; sp = 1152; bytes = 1152; bar = B_W2 + j; ebar = B_VDONE;
                when = T_K + T_V + T_O + T_G + T_G2 + 6 * TAU_1 + (j < 2 ? j * TAU_2A : 2 * TAU_2A + (j - 2) * TAU_2B);
            }
            if (ebar >= 0) { mbar_wait(bars + 8 * ebar); asm volatile("fence.proxy.async.shared::cta;" ::: "memory"); }
            const int dep = s - (s < sO ? WIN_CAP : s < s1 ? CAP_O : s < s2 ? CAP_1 : CAP_2);
            if (dep >= 0) mbar_wait(bars + 8 * (dep < sV ? B_K + dep : dep < sO ? B_V + dep - sV : dep < s1 ? B_WO + dep - sO : B_W1 + dep - s1));
            const unsigned t_go = t_start + PACE_T0 + when;
            for (int it = 0; it < 100000; it++) {
                unsigned now; asm volatile("mov.u32 %0, %%globaltimer_lo;" : "=r"(now));
                if ((int)(now - t_go) >= 0) break;
            }
            if (elect()) {
                const int nh = bytes == 576 ? 2 : 1;
#pragma unroll 1
                for (int h = 0; h < nh; h++) issue8(sb + dst + 8 * h * dp, dp, src + (size_t)(8 * h) * sp, sp, bytes, bars + 8 * bar, pol);
            }
            __syncwarp();
        }
        asm volatile("barrier.cluster.wait.aligned;" ::: "memory");
    } else if (warp >= EW0) {
        const int e = warp - EW0, et = tid - EW0 * 32;
        asm volatile("barrier.cluster.wait.aligned;" ::: "memory");
        if (e == 2) {
            if (lane == 0) {
                const unsigned target = (arrived / NCTA + 1) * NCTA;
                for (unsigned it = 0; (int)(++arrived - target) < 0; it++) {
                    asm volatile("ld.acquire.gpu.global.u32 %0, [%1];" : "=r"(arrived) : "l"(G_ARRIVE) : "memory");
                    arrived--;
                    if (it > 0x400000u) __trap();
                }
                mbar_arrive(bars + 8 * B_INIT);
            }
            __syncwarp();
            TL(22);
        }
        if (e < 2) {
            mbar_wait(bars + 8 * B_X1);
            float a0 = 0.f, a1 = 0.f, a2 = 0.f, a3 = 0.f;
#pragma unroll
            for (int s = 0; s < CS; s++) {
                const uint4 v = lds128(sb + X1R + s * 1024 + et * 16);
                a0 += __uint_as_float(v.x); a1 += __uint_as_float(v.y); a2 += __uint_as_float(v.z); a3 += __uint_as_float(v.w);
            }
            const int w = et >> 2;
            const uint32_t qa = sb + Q_S + ((w >> 3) * 4 + (et & 3)) * 80 + (w & 7) * 8, q0 = pack2(a0, a2), q1 = pack2(a1, a3);
            sts64(qa, q0, q1); sts64(qa + 640, q1, q0);
            __syncwarp();
            if (lane == 0) mbar_arrive(bars + 8 * B_Q);
            if (e == 0) TL(3);
            mbar_wait(bars + 8 * B_X2);
            if (et < 8 * nO) {
                const int head = (u0 + (et >> 3)) >> 4;
                float m[CS], l[CS], o[CS];
#pragma unroll
                for (int s = 0; s < CS; s++) {
                    const uint2 v = lds64(sb + X2S + s * 16 + head * 8);
                    m[s] = __uint_as_float(v.x); l[s] = __uint_as_float(v.y);
                    o[s] = ldsf(sb + X2R + (s * 48 + et) * 4);
                }
                float M = m[0];
#pragma unroll
                for (int s = 1; s < CS; s++) M = fmaxf(M, m[s]);
                float L = 0.f, acc = 0.f;
#pragma unroll
                for (int s = 0; s < CS; s++) { const float ws = ex2((m[s] - M) * LOG2E); L += ws * l[s]; acc += ws * o[s]; }
                sts16(sb + O_S + 2 * et, f2bf(__fdividef(acc, L)));
            }
            __syncwarp();
            if (lane == 0) mbar_arrive(bars + 8 * B_O);
            if (e == 0) TL(4);
        }
        {
            uint32_t* p3 = pin(reinterpret_cast<uint32_t*>(g_slot3) + r * NCL * (STR3 * 32) + et);
            uint32_t* pw = pin(p3 + c * (STR3 * 32));
            const float xres = __bfloat162float(__ldg(gx + 96 * r + et));
            const int lc = et;
            const uint32_t hdst = pin(sb + H_S + 2 * pos16(lc));
            mbar_wait(bars + 8 * B_INIT);
            mbar_wait(bars + 8 * B_X3);
            {
                float a[CS];
#pragma unroll
                for (int s = 0; s < CS; s++) a[s] = ldsf(sb + X3R + (s * 96 + et) * 4);
                publish<RED3>(pw, ((a[0] + a[1]) + (a[2] + a[3])) + (a[4] + a[5]));
            }
            if (e == 0) TL(5);
            const float attn = gather_sum<NCL>(p3, STR3 * 32, ATOM_TH);
            TL(6 + 14 * (e > 0) + (e > 1));
            const float h = bfr(xres + bfr(attn));
            sts16(hdst, (uint16_t)(__float_as_uint(h) >> 16));
            stsf(sb + HF_S + 4 * lc, h);
            asm volatile("bar.arrive 4, %0;" ::"n"(NMMA * 32 + 96) : "memory");
            __syncwarp();
            if (lane == 0) mbar_arrive(bars + 8 * B_H);
            TL(53 + e);
            const float k0 = __shfl_sync(0xFFFFFFFFu, h, 0);
            float s = h - k0, q = s * s;
#pragma unroll
            for (int m = 16; m; m >>= 1) { s += shx(s, m); q += shx(q, m); }
            if (lane < CS) st_async4(mapa(sb + X4S + (r * 3 + e) * 16, lane), k0, s, q, 0.f, mapa(bars + 8 * B_X4S, lane));
        }
        {
            mbar_wait(bars + 8 * B_X4S);
            if (e == 0) TL(26);
            const float kc = ldsf(sb + X4S);
            const uint4 st = lds128(sb + X4S + (lane < 18 ? lane : 0) * 16);
            const float dk = __uint_as_float(st.x) - kc, gs = __uint_as_float(st.y);
            float s = lane < 18 ? gs + 32.0f * dk : 0.f;
            float q = lane < 18 ? __uint_as_float(st.z) + dk * (2.0f * gs + 32.0f * dk) : 0.f;
#pragma unroll
            for (int m = 16; m; m >>= 1) { s += shx(s, m); q += shx(q, m); }
            const float dm = s * (1.0f / DM);
            const float var = fmaxf(q * (1.0f / DM) - dm * dm, 0.f);
            const float mb = bfr(kc + dm), rsd = __fdividef(1.0f, bfr(sqrt_fast(bfr(bfr(var) + 1e-5f))));
            mbar_wait(bars + 8 * B_X4);
            if (e == 0) TL(7);
            const int f = 16 * e + (lane >> 1);
            float s1 = 0.f, s2 = 0.f;
#pragma unroll
            for (int i = 0; i < 3; i++) {
                const uint2 v = lds64(sb + X4R + ((3 * (lane & 1) + i) * 48 + f) * 8);
                s1 += __uint_as_float(v.x); s2 += __uint_as_float(v.y);
            }
            float pre = s1 - mb * s2;
            pre = bfr((pre + shx(pre, 1)) * rsd);
            const float act = __fdividef(pre, 1.0f + ex2(-pre * LOG2E));
            if (!(lane & 1)) sts16(sb + H1_S + 2 * f, f2bf(act));
            asm volatile("bar.arrive 5, %0;" ::"n"(NMMA * 32 + 96) : "memory");
            TL(56 + e);
        }
        if (e == 0 && c < 12) {
            TL(8);
            const uint4* p5 = pin(g_slot5 + (r * 12 + c) * (STR5 * 8) + lane);
            const int lc = 8 * c + 4 * (lane & 1) + 2 * (lane >> 4) + ((lane >> 3) & 1);
            uint16_t* pout = pin(reinterpret_cast<uint16_t*>(gout) + 96 * r + lc);
            mbar_wait(bars + 8 * B_H);
            const float hres = ldsf(sb + HF_S + 4 * lc);
            uint4 v[6];
#pragma unroll
            for (int k = 0; k < 6; k++) v[k] = ldg_rlx128(p5 + k * 32);
            float a0, a1, a2, a3;
            for (unsigned it = 0;; it++) {
#define SUM6(f) (((__uint_as_float(v[0].f) + __uint_as_float(v[1].f)) + (__uint_as_float(v[2].f) + __uint_as_float(v[3].f))) + (__uint_as_float(v[4].f) + __uint_as_float(v[5].f)))
                a0 = SUM6(x); a1 = SUM6(y); a2 = SUM6(z); a3 = SUM6(w);
#undef SUM6
                const float chk = (a0 + a1) + (a2 + a3);
                if (!__any_sync(0xFFFFFFFFu, chk != chk)) break;
                bool miss = false;
#pragma unroll
                for (int k = 0; k < 6; k++) { const bool m = has_sent(v[k]); miss |= m; ldg_rlx128_if(v[k], p5 + k * 32, m); }
                if (!__any_sync(0xFFFFFFFFu, miss)) break;
                if (it > 0x400000u) __trap();
            }
            TL(9);
            const bool h16 = lane & 16, h8 = lane & 8;
            const float b0 = (h16 ? a2 : a0) + shx(h16 ? a0 : a2, 16), b1 = (h16 ? a3 : a1) + shx(h16 ? a1 : a3, 16);
            float y = (h8 ? b1 : b0) + shx(h8 ? b0 : b1, 8);
            y += shx(y, 4); y += shx(y, 2);
            if (!(lane & 6)) *pout = f2bf(hres + bfr(y));
            TL(10);
        }
    } else {
        const int w = warp;
        const int cx = ((lane >> 3) ^ (lane >> 2)) & 1;
        const bool act = (t >> 1) == (g & 1);
        if (w < 16) {
            uint2 b[6];
#pragma unroll
            for (int ks = 0; ks < 6; ks++) b[ks] = lds64(sb + (act ? XN_S : ZERO_S) + (ks * 4 + t) * 8);
            float acc[2][4] = {};
            const uint32_t ab = sb + WQ_OFF + ((lane & 7) + 8 * (lane >> 4)) * WQ_PITCH + (2 * w + cx) * 16;
#pragma unroll
            for (int ks = 0; ks < 6; ks++) {
                mbar_wait(bars + 8 * (B_WQ + 2 * ks)); mbar_wait(bars + 8 * (B_WQ + 2 * ks + 1));
                uint32_t a[4]; ldsm4t(a, ab + ks * WQ_STAGE);
                mma16(acc[ks & 1], a, b[ks].x, b[ks].y);
            }
            const float c0 = (acc[0][0] + acc[1][0]) + (acc[0][3] + acc[1][3]), c2 = (acc[0][2] + acc[1][2]) + (acc[0][1] + acc[1][1]);
            if (w == 0) TL(11);
            asm volatile("barrier.cluster.wait.aligned;" ::: "memory");
            const uint32_t da = sb + X1R + r * 1024 + (w * 8 + g) * 8;
            st_async2(mapa(da, t), c0, c2, mapa(bars + 8 * B_X1, t));
            if (t < 2) st_async2(mapa(da, t + 4), c0, c2, mapa(bars + 8 * B_X1, t + 4));
            if (lane == 0) mbar_arrive(bars + 8 * B_WQDONE);
        } else {
            asm volatile("barrier.cluster.wait.aligned;" ::: "memory");
        }
        const int head = t & 1, half = t >> 1;
        float sc[2];
        {
            mbar_wait(bars + 8 * B_Q);
            uint32_t qb[16];
#pragma unroll
            for (int j = 0; j < 4; j++) {
                const uint4 v = lds128(sb + Q_S + (((g >> 1) & 1) * 8 + (g & 1) * 4 + t) * 80 + j * 16);
                qb[4 * j] = v.x; qb[4 * j + 1] = v.y; qb[4 * j + 2] = v.z; qb[4 * j + 3] = v.w;
            }
#pragma unroll
            for (int it = 0; it < 2; it++) {
                const int tau = w + NMMA * it;
                sc[it] = -INFINITY;
                if (tau < 2 * nK) {
                    mbar_wait(bars + 8 * (B_K + (tau >> 1)));
                    const uint32_t ab = sb + K_OFF + (tau >> 1) * KV_STAGE + (lane & 7) * KV_GRP + ((tau & 1) * 2 + ((lane >> 3) & 1)) * 256 + (((lane >> 4) ^ (lane >> 2)) & 1) * 16;
                    float acc[2][4] = {};
#pragma unroll
                    for (int ks = 0; ks < 8; ks++) {
                        uint32_t a[4]; ldsm4(a, ab + ks * 32);
                        mma16(acc[ks & 1], a, qb[2 * ks], qb[2 * ks + 1]);
                    }
                    const float x0 = half ? acc[0][2] + acc[1][2] : acc[0][0] + acc[1][0], x1 = half ? acc[0][3] + acc[1][3] : acc[0][1] + acc[1][1];
                    const float other = shx(head ? x0 : x1, 1);
                    const float raw = head == (g >> 2) ? (head ? x1 : x0) : other;
                    sc[it] = bfr(bfr(raw) * 0.08838834764831845f);
                }
            }
        }
        float M = fmaxf(sc[0], sc[1]);
#pragma unroll
        for (int m = 2; m <= 16; m <<= 1) M = fmaxf(M, shx(M, m));
        if (lane < 2) stsf(sb + WMAX + (2 * w + lane) * 4, M);
        if (lane == 0) mbar_arrive(bars + 8 * B_KDONE);
        if (w == 0) TL(12);
        bar_mma();
        M = ldsf(sb + WMAX + lane * 4);
        if (lane < 4) M = fmaxf(M, ldsf(sb + WMAX + (32 + lane) * 4));
#pragma unroll
        for (int m = 2; m <= 16; m <<= 1) M = fmaxf(M, shx(M, m));
        {
            float ls = 0.f;
#pragma unroll
            for (int it = 0; it < 2; it++) {
                const int tau = w + NMMA * it;
                if (tau < 2 * nK) {
                    const float pb = bfr(ex2((sc[it] - M) * LOG2E));
                    ls += pb;
                    sts16(sb + P_S + head * 704 + (tau * 16 + (g >> 1) * 4 + half * 2 + (g & 1)) * 2, (uint16_t)(__float_as_uint(pb) >> 16));
                }
            }
#pragma unroll
            for (int m = 2; m <= 16; m <<= 1) ls += shx(ls, m);
            if (lane < 2) stsf(sb + WSUM + (2 * w + lane) * 4, ls);
        }
        bar_mma();
        if (w == 8) {
            float L = ldsf(sb + WSUM + lane * 4);
            if (lane < 4) L += ldsf(sb + WSUM + (32 + lane) * 4);
#pragma unroll
            for (int m = 2; m <= 16; m <<= 1) L += shx(L, m);
            const float Mo = shx(M, 1), Lo = shx(L, 1);
            if (lane < CS) st_async4(mapa(sb + X2S + r * 16, lane), head ? Mo : M, head ? Lo : L, head ? M : Mo, head ? L : Lo, mapa(bars + 8 * B_X2, lane));
            TL(13);
        }
        if (w < 8) {
            float acc[2][4] = {};
            const uint32_t ao = sb + (lane & 7) * KV_GRP + (lane >> 4) * 256 + (2 * w + cx) * 16;
            const uint32_t pb = sb + P_S + (g & 1) * 704 + t * 8;
            const uint32_t pm = (t >> 1) == ((g >> 1) & 1) ? 0xFFFFFFFFu : 0u;
#pragma unroll
            for (int j = 0; j < 11; j++) {
                if (j < nK) {
                    const uint2 b0 = lds64(pb + j * 64), b1 = lds64(pb + j * 64 + 32);
                    mbar_wait(bars + 8 * (B_V + j));
                    const uint32_t ab = ao + (j < 8 ? V_OFF + j * KV_STAGE : (j - 8) * KV_STAGE);
                    uint32_t a0[4], a1[4];
                    ldsm4t(a0, ab); ldsm4t(a1, ab + 512);
                    mma16(acc[0], a0, b0.x & pm, b0.y & pm);
                    mma16(acc[1], a1, b1.x & pm, b1.y & pm);
                    if (j == 6 && lane == 0) mbar_arrive(bars + 8 * B_VDONE);
                }
            }
            const float own = half ? acc[0][1] + acc[1][1] : acc[0][0] + acc[1][0], snd = half ? acc[0][3] + acc[1][3] : acc[0][2] + acc[1][2];
            const float val = own + shx(snd, 1);
            const int u = 16 * half + 2 * w + head;
            const int dest = u < 20 ? u / 5 : (u < 26 ? 4 : 5);
            const int ud = u - (dest < 5 ? 5 * dest : 26);
            st_async1(mapa(sb + X2R + (r * 48 + ud * 8 + g) * 4, dest), val, mapa(bars + 8 * B_X2, dest));
            if (w == 0) TL(14);
        }
        const int rd = w / 3, jd = w - 3 * rd;
        const uint32_t wro = pin(sb + (lane & 7) * WR_PITCH + (lane >> 4) * WR_STAGE + (4 * w + cx) * 16);
        {
            const uint32_t da = mapa(sb + X3R + (r * 96 + 32 * jd + 8 * t + g) * 4, rd), db = mapa(bars + 8 * B_X3, rd);
            mbar_wait(bars + 8 * B_O);
            uint32_t b[6];
#pragma unroll
            for (int u = 0; u < 6; u++) b[u] = lds32(sb + (act ? O_S : ZERO_S) + (8 * u + 2 * t) * 2);
            if (nO == 5) b[5] = 0;
            float accA[4] = {}, accB[4] = {};
#pragma unroll
            for (int u = 0; u < 6; u += 2) {
                mbar_wait(bars + 8 * (B_WO + u));
                uint32_t ad = wro + WO_OFF + u * WR_STAGE, a0[4], a1[4];
                if (u + 1 < nO) mbar_wait(bars + 8 * (B_WO + u + 1));
                else ad -= (lane >> 4) * WR_STAGE;
                ldsm4t(a0, ad); ldsm4t(a1, ad + 32);
                mma16(accA, a0, b[u], b[u + 1]);
                mma16(accB, a1, b[u], b[u + 1]);
            }
            st_async1(da, pick4(accA[0], accA[2], accB[0], accB[2], t) + pick4(accA[3], accA[1], accB[3], accB[1], t), db);
            if (w == 0) TL(15);
        }
        {
            uint32_t a[6][4];
            float cs[4] = {};
            const uint32_t ab = sb + W1_OFF + ((lane & 7) + 8 * (lane >> 4)) * W1_PITCH + (2 * w + cx) * 16;
            const uint32_t ones = act ? 0x3F803F80u : 0u;
#pragma unroll
            for (int ks = 0; ks < 6; ks++) { mbar_wait(bars + 8 * (B_W1 + ks)); ldsm4t(a[ks], ab + ks * W1_STAGE); mma16(cs, a[ks], ones, ones); }
            const float s2 = (t & 1) ? cs[2] + cs[1] : cs[0] + cs[3];
            const uint32_t hb = pin(sb + (act ? H_S : ZERO_S) + t * 8);
            const uint32_t da = pin(mapa(sb + X4R + (r * 48 + 16 * jd + 8 * (t & 1) + g) * 8, rd)), db = pin(mapa(bars + 8 * B_X4, rd));
            if (w == 0) TL(16);
            asm volatile("bar.sync 4, %0;" ::"n"(NMMA * 32 + 96) : "memory");
            if (w == 0) TL(28);
            float acc[2][4] = {};
#pragma unroll
            for (int ks = 0; ks < 6; ks++) {
                const uint2 b = lds64(hb + ks * 32);
                mma16(acc[ks & 1], a[ks], b.x, b.y);
            }
            if (t < 2) {
                const float s1 = t ? (acc[0][2] + acc[1][2]) + (acc[0][1] + acc[1][1]) : (acc[0][0] + acc[1][0]) + (acc[0][3] + acc[1][3]);
                st_async2(da, s1, s2, db);
            }
            __syncwarp();
            if (w == 0) TL(24);
            if (w == 17) TL(25);
        }
        {
            float* pw = pin(reinterpret_cast<float*>(g_slot5) + (4 * w + t) * (STR5 * 32) + blockIdx.x * 8 + g);
            const uint32_t hb = pin(sb + (act ? H1_S : ZERO_S) + t * 4);
            uint32_t a[4][4];
#pragma unroll
            for (int u = 0; u < 4; u += 2) {
                mbar_wait(bars + 8 * (B_W2 + u)); mbar_wait(bars + 8 * (B_W2 + u + 1));
                ldsm4t(a[u], wro + W2_OFF + u * WR_STAGE); ldsm4t(a[u + 1], wro + W2_OFF + u * WR_STAGE + 32);
            }
            if (w == 0) TL(27);
            asm volatile("bar.sync 5, %0;" ::"n"(NMMA * 32 + 96) : "memory");
            if (w == 0) TL(29);
            uint32_t b[6];
#pragma unroll
            for (int u = 0; u < 6; u++) b[u] = lds32(hb + 16 * u);
            float accA[4] = {}, accB[4] = {};
            mma16(accA, a[0], b[0], b[1]); mma16(accB, a[1], b[0], b[1]);
            mma16(accA, a[2], b[2], b[3]); mma16(accB, a[3], b[2], b[3]);
            mbar_wait(bars + 8 * (B_W2 + 4)); mbar_wait(bars + 8 * (B_W2 + 5));
            if (w == 0) TL(17);
            ldsm4t(a[0], wro + W2_OFF + 4 * WR_STAGE); ldsm4t(a[1], wro + W2_OFF + 4 * WR_STAGE + 32);
            mma16(accA, a[0], b[4], b[5]); mma16(accB, a[1], b[4], b[5]);
            publish<RED5>(pw, pick4(accA[0], accA[2], accB[0], accB[2], t) + pick4(accA[3], accA[1], accB[3], accB[1], t));
            TL(32 + w);
        }
    }
}

}

extern "C" void kernel_launch(void* const* d_in, const int* in_sizes, int n_in, void* d_out, int out_size) {
    (void)in_sizes; (void)n_in; (void)out_size;
    static bool configured = false;
    static Scratch* scr = nullptr;
    if (!configured) {
        cudaFuncSetAttribute(fused_decode_kernel, cudaFuncAttributeMaxDynamicSharedMemorySize, SMEM_BYTES);
        cudaGetSymbolAddress((void**)&scr, g_scratch);
        configured = true;
    }
    fused_decode_kernel<<<NCTA, NTHREADS, SMEM_BYTES>>>(
        (const __nv_bfloat16*)d_in[0], (const char*)d_in[1], (const char*)d_in[2], (const char*)d_in[3],
        (const char*)d_in[4], (const char*)d_in[6], (const char*)d_in[7], (__nv_bfloat16*)d_out, scr
    );
}
```

```cpp
#include <cuda.h>
#include <cuda_runtime.h>
#include <cuda_bf16.h>
#include <stdint.h>

namespace {

constexpr int DM = 576, SK = 8192, WIN = 2048, FF = 4608;
constexpr int CS = 6, NCL = 16, NCTA = CS * NCL;
constexpr int NMMA = 18;
constexpr int EW0 = 18;
constexpr int PW0 = 21, NPROD = 2;
constexpr int NTHREADS = (PW0 + NPROD) * 32;
constexpr int NCPA = 2;
constexpr int W1PRE = 4;

constexpr int PACE_T0 = 600, T_K = 2640, T_V = 2665, T_O = 1680, TAU_1 = 268, TAU_2A = 250, TAU_2B = 200;
constexpr int WIN_CAP = 9, CAP_O = 8, CAP_1 = 10, CAP_2 = 10;

constexpr int WQ_PITCH = 544, KV_GRP = 1056, KV_STAGE = 8 * KV_GRP, WR_PITCH = 1184, WR_STAGE = 8 * WR_PITCH;
constexpr int W1_PITCH = 608, W1_STAGE = 16 * W1_PITCH, WQ_STAGE = 16 * WQ_PITCH;
constexpr int WQ_OFF = 0;
constexpr int K_OFF = 96 * WQ_PITCH;
constexpr int V_OFF = K_OFF + 11 * KV_STAGE;
constexpr int RING_END = V_OFF + 8 * KV_STAGE;
constexpr int WO_OFF = 3 * KV_STAGE;
constexpr int W1_OFF = WO_OFF + 6 * WR_STAGE;
constexpr int W2_OFF = (W1_OFF + 6 * W1_STAGE + 511) / 512 * 512, W2_STAGE = 9216;
static_assert(W2_OFF + 6 * W2_STAGE <= V_OFF + 7 * KV_STAGE, "w2 must only overlap V stages 0..6");
static_assert(WO_OFF + 2 * WR_STAGE <= K_OFF && W1_OFF + 6 * W1_STAGE <= V_OFF, "wo / w1 placement");
constexpr int X1R = RING_END;
constexpr int X2R = X1R + 6144;
constexpr int X2S = X2R + 1152;
constexpr int X3R = X2S + 96;
constexpr int X4R = X3R + 2304;
constexpr int X4S = X4R + 2304;
constexpr int Q_S = X4S + 288;
constexpr int XN_S = Q_S + 1280;
constexpr int P_S = XN_S + 192;
constexpr int WMAX = P_S + 1408;
constexpr int WSUM = WMAX + 160;
constexpr int O_S = WSUM + 160;
constexpr int H_S = O_S + 96;
constexpr int ZERO_S = H_S + 192;
constexpr int H1G = ZERO_S + 192;
constexpr int XSC_S = H1G + 576;
constexpr int BARS = XSC_S + 16;
constexpr int B_WQ = 0, B_K = 12, B_V = 23, B_WO = 34, B_W1 = 40, B_W2 = 46;
constexpr int B_WQDONE = 52, B_KDONE = 53, B_VDONE = 54;
constexpr int B_X1 = 55, B_X2 = 56, B_X3 = 57, B_X4 = 58, B_X4S = 59;
constexpr int B_Q = 60, B_O = 61, B_INIT = 62, B_H1G = 63;
constexpr int NBAR = 64;
constexpr int SMEM_BYTES = BARS + NBAR * 8;
static_assert(BARS % 8 == 0 && X2S % 16 == 0 && Q_S % 16 == 0 && X4R % 16 == 0 && X1R % 16 == 0, "align");
static_assert(SMEM_BYTES <= 232448, "smem");

constexpr unsigned SPIN_LIMIT = 0x200000;
constexpr uint32_t SENT = 0xFFFFFFFFu;

struct __align__(256) Scratch {
    unsigned long long acc[2][640];
    uint4 side[2][CS * NCL * 24];
    unsigned arrive;
};
__device__ Scratch g_scratch;
#define G_ARRIVE (&scr->arrive)

__device__ __forceinline__ void mbar_init(uint32_t b, uint32_t c) { asm volatile("mbarrier.init.shared::cta.b64 [%0], %1;" ::"r"(b), "r"(c) : "memory"); }
__device__ __forceinline__ void mbar_expect(uint32_t b, uint32_t bytes) { asm volatile("mbarrier.arrive.expect_tx.shared::cta.b64 _, [%0], %1;" ::"r"(b), "r"(bytes) : "memory"); }
__device__ __forceinline__ void mbar_arrive(uint32_t b) { asm volatile("mbarrier.arrive.shared::cta.b64 _, [%0];" ::"r"(b) : "memory"); }
__device__ __forceinline__ void mbar_wait(uint32_t b) {
    asm volatile("{\n.reg .pred p;\n.reg .u32 n;\nmov.u32 n, 0;\n"
                 "W_LOOP:\nmbarrier.try_wait.parity.shared::cta.b64 p, [%0], 0;\n@p bra W_DONE;\n"
                 "add.u32 n, n, 1;\nsetp.lt.u32 p, n, 0x200000;\n@p bra W_LOOP;\ntrap;\nW_DONE:\n}" ::"r"(b) : "memory");
}
__device__ __forceinline__ bool elect() { uint32_t p; asm volatile("{.reg .pred P; elect.sync _|P, 0xffffffff; selp.u32 %0,1,0,P;}" : "=r"(p)); return p; }
__device__ __forceinline__ float ex2(float x) { float y; asm("ex2.approx.ftz.f32 %0, %1;" : "=f"(y) : "f"(x)); return y; }
__device__ __forceinline__ float sqrt_fast(float x) { float y; asm("sqrt.approx.f32 %0, %1;" : "=f"(y) : "f"(x)); return y; }
__device__ __forceinline__ void bulk_g2s(uint32_t dst, const void* src, uint32_t bytes, uint32_t bar, uint64_t pol) {
    asm volatile("cp.async.bulk.shared::cluster.global.mbarrier::complete_tx::bytes.L2::cache_hint [%0], [%1], %2, [%3], %4;" ::"r"(dst), "l"(src), "r"(bytes), "r"(bar), "l"(pol) : "memory");
}
__device__ __forceinline__ void tma3(uint32_t dst, const CUtensorMap* m, int blk, int row, uint32_t bar, uint64_t pol) {
    asm volatile("cp.async.bulk.tensor.3d.shared::cluster.global.mbarrier::complete_tx::bytes.L2::cache_hint [%0], [%1, {0, %2, %3}], [%4], %5;"
                 ::"r"(dst), "l"(m), "r"(blk), "r"(row), "r"(bar), "l"(pol) : "memory");
}
__device__ __forceinline__ uint32_t mapa(uint32_t a, uint32_t rank) { uint32_t r; asm("mapa.shared::cluster.u32 %0, %1, %2;" : "=r"(r) : "r"(a), "r"(rank)); return r; }
__device__ __forceinline__ void st_async1(uint32_t a, float v, uint32_t bar) { asm volatile("st.async.shared::cluster.mbarrier::complete_tx::bytes.b32 [%0], %1, [%2];" ::"r"(a), "r"(__float_as_uint(v)), "r"(bar) : "memory"); }
__device__ __forceinline__ void st_async2(uint32_t a, float x, float y, uint32_t bar) { asm volatile("st.async.shared::cluster.mbarrier::complete_tx::bytes.v2.b32 [%0], {%1,%2}, [%3];" ::"r"(a), "r"(__float_as_uint(x)), "r"(__float_as_uint(y)), "r"(bar) : "memory"); }
__device__ __forceinline__ void st_async4(uint32_t a, float x, float y, float z, float w, uint32_t bar) { asm volatile("st.async.shared::cluster.mbarrier::complete_tx::bytes.v4.b32 [%0], {%1,%2,%3,%4}, [%5];" ::"r"(a), "r"(__float_as_uint(x)), "r"(__float_as_uint(y)), "r"(__float_as_uint(z)), "r"(__float_as_uint(w)), "r"(bar) : "memory"); }
__device__ __forceinline__ void ldsm4(uint32_t (&r)[4], uint32_t a) { asm volatile("ldmatrix.sync.aligned.m8n8.x4.shared.b16 {%0,%1,%2,%3}, [%4];" : "=r"(r[0]), "=r"(r[1]), "=r"(r[2]), "=r"(r[3]) : "r"(a) : "memory"); }
__device__ __forceinline__ void ldsm4t(uint32_t (&r)[4], uint32_t a) { asm volatile("ldmatrix.sync.aligned.m8n8.x4.trans.shared.b16 {%0,%1,%2,%3}, [%4];" : "=r"(r[0]), "=r"(r[1]), "=r"(r[2]), "=r"(r[3]) : "r"(a) : "memory"); }
__device__ __forceinline__ void mma16(float (&c)[4], const uint32_t (&a)[4], uint32_t b0, uint32_t b1) {
    asm volatile("mma.sync.aligned.m16n8k16.row.col.f32.bf16.bf16.f32 {%0,%1,%2,%3}, {%4,%5,%6,%7}, {%8,%9}, {%0,%1,%2,%3};"
                 : "+f"(c[0]), "+f"(c[1]), "+f"(c[2]), "+f"(c[3]) : "r"(a[0]), "r"(a[1]), "r"(a[2]), "r"(a[3]), "r"(b0), "r"(b1));
}
__device__ __forceinline__ uint32_t lds32(uint32_t a) { uint32_t v; asm volatile("ld.shared.b32 %0, [%1];" : "=r"(v) : "r"(a) : "memory"); return v; }
__device__ __forceinline__ float ldsf(uint32_t a) { return __uint_as_float(lds32(a)); }
__device__ __forceinline__ uint2 lds64(uint32_t a) { uint2 v; asm volatile("ld.shared.v2.b32 {%0,%1}, [%2];" : "=r"(v.x), "=r"(v.y) : "r"(a) : "memory"); return v; }
__device__ __forceinline__ uint4 lds128(uint32_t a) { uint4 v; asm volatile("ld.shared.v4.b32 {%0,%1,%2,%3}, [%4];" : "=r"(v.x), "=r"(v.y), "=r"(v.z), "=r"(v.w) : "r"(a) : "memory"); return v; }
__device__ __forceinline__ void sts16(uint32_t a, uint16_t v) { asm volatile("st.shared.b16 [%0], %1;" ::"r"(a), "h"(v) : "memory"); }
__device__ __forceinline__ void stsf(uint32_t a, float v) { asm volatile("st.shared.f32 [%0], %1;" ::"r"(a), "f"(v) : "memory"); }
__device__ __forceinline__ void sts64(uint32_t a, uint32_t x, uint32_t y) { asm volatile("st.shared.v2.b32 [%0], {%1,%2};" ::"r"(a), "r"(x), "r"(y) : "memory"); }
__device__ __forceinline__ void publish(void* p, float v) {
    uint32_t u = __float_as_uint(v);
    u = (u == SENT) ? 0x7FFFFFFFu : u;
    asm volatile("red.relaxed.gpu.global.and.b32 [%0], %1;" ::"l"(p), "r"(u) : "memory");
}
__device__ __forceinline__ uint32_t pack2(float lo, float hi) { uint32_t d; asm("cvt.rn.bf16x2.f32 %0, %1, %2;" : "=r"(d) : "f"(hi), "f"(lo)); return d; }
__device__ __forceinline__ uint16_t f2bf(float v) { return (uint16_t)pack2(v, 0.f); }
__device__ __forceinline__ float bfr(float v) { return __uint_as_float(pack2(0.f, v)); }
template <typename T> __device__ __forceinline__ T* pin(T* p) { asm volatile("" : "+l"(p)); return p; }
__device__ __forceinline__ float pinf(float a) { asm volatile("" : "+f"(a)); return a; }
__device__ __forceinline__ uint32_t pin(uint32_t a) { asm volatile("" : "+r"(a)); return a; }
__device__ __forceinline__ float bflo(uint32_t u) { return __uint_as_float(u << 16); }
__device__ __forceinline__ float bfhi(uint32_t u) { return __uint_as_float(u & 0xFFFF0000u); }
__device__ __forceinline__ float shx(float v, int m) { return __shfl_xor_sync(0xFFFFFFFFu, v, m); }
__device__ __forceinline__ float pick4(float a, float b, float c, float d, int t) { float x = (t & 1) ? b : a, y = (t & 1) ? d : c; return (t & 2) ? y : x; }
__device__ __forceinline__ void bar_mma() { asm volatile("bar.sync 1, %0;" ::"n"(NMMA * 32) : "memory"); }
__device__ __forceinline__ void issue8(uint32_t dst, uint32_t dpitch, const char* src, uint32_t spitch, uint32_t bytes, uint32_t bar, uint64_t pol) {
#pragma unroll
    for (int i = 0; i < 8; i++) bulk_g2s(dst + i * dpitch, src + (size_t)i * spitch, bytes, bar, pol);
}
__device__ __forceinline__ uint32_t ld_read(const uint32_t* p) { uint32_t v; asm volatile("ld.relaxed.gpu.global.b32 %0, [%1];" : "=r"(v) : "l"(p) : "memory"); return v; }
struct Fix { float up, down, lim; };
__device__ __forceinline__ Fix make_fix(float scale) {
    const uint32_t eb = min(max(__float_as_uint(scale) >> 23, 47u), 207u);
    return {pinf(__uint_as_float((280u - eb) << 23)), pinf(__uint_as_float((eb - 26u) << 23)), pinf(__uint_as_float((eb + 22u) << 23))};
}
__device__ __forceinline__ unsigned long long atom_add64(unsigned long long* p, unsigned long long v) {
    unsigned long long o; asm volatile("atom.relaxed.gpu.global.add.u64 %0, [%1], %2;" : "=l"(o) : "l"(p), "l"(v) : "memory"); return o;
}
__device__ __forceinline__ unsigned long long fix_add(unsigned long long* pa, uint32_t* side_mine, float part, const Fix& f) {
    long long fx;
    asm volatile("cvt.rni.s64.f32 %0, %1;" : "=l"(fx) : "f"(part * f.up));
    const bool big = !(fabsf(part) < f.lim);
    const unsigned long long add = big ? 33ull : ((unsigned long long)fx << 10) + 1ull;
    const unsigned long long old = atom_add64(pa, add);
    if (big) publish(side_mine, part);
    return old + add;
}
__device__ __forceinline__ float fix_value(unsigned long long tot, const uint32_t* side_col, const Fix& f) {
    float y = __ll2float_rn((long long)tot >> 10) * f.down;
    const unsigned nbig = (unsigned)(tot >> 5) & 31;
    if (__builtin_expect(nbig != 0, 0)) {
        for (unsigned it = 0;; it++) {
            float z = y; unsigned n = 0;
#pragma unroll 1
            for (int k = 0; k < NCL; k++) { const uint32_t v = ld_read(side_col + k * 96); if (v != SENT) { z += __uint_as_float(v); n++; } }
            if (n == nbig) return z;
            if (it > SPIN_LIMIT) __trap();
        }
    }
    return y;
}
__device__ __forceinline__ int pos16(int k) { return (k & ~15) + ((k & 7) >> 1) * 4 + ((k >> 3) & 1) * 2 + (k & 1); }

constexpr float LOG2E = 1.4426950408889634f;

__global__ void __cluster_dims__(CS, 1, 1) __launch_bounds__(NTHREADS, 1)
fused_decode_kernel(const __nv_bfloat16* __restrict__ gx, const char* __restrict__ gk, const char* __restrict__ gv,
                    const char* __restrict__ gwq, const char* __restrict__ gwo, const char* __restrict__ gw1,
                    __nv_bfloat16* __restrict__ gout, Scratch* __restrict__ scr, const int pace,
                    const __grid_constant__ CUtensorMap m2) {
    extern __shared__ __align__(1024) unsigned char smem_raw[];
    const uint32_t sb = pin((uint32_t)__cvta_generic_to_shared(smem_raw));
    const uint32_t bars = sb + BARS;
    const int tid = threadIdx.x, lane = tid & 31;
    const int c = blockIdx.y, r = blockIdx.x;
    const int cta = c * CS + r;
    const uint64_t pol = 0x12F0000000000000ull;
    uint4 wq_r[NCPA];
    {
        const char* pw = gwq + ((uint32_t)(96 * r) * 8192u + (uint32_t)(512 * c) + (uint32_t)(tid >> 5) * 8192u + (uint32_t)lane * 16u);
#pragma unroll
        for (int i = 0; i < NCPA; i++)
            asm volatile("{.reg .pred p; setp.lt.u32 p, %6, 512; @p ld.global.nc.L1::no_allocate.L2::cache_hint.v4.b32 {%0,%1,%2,%3}, [%4], %5;}"
                         : "=r"(wq_r[i].x), "=r"(wq_r[i].y), "=r"(wq_r[i].z), "=r"(wq_r[i].w) : "l"(pw + i * (16 * 8192)), "l"(pol), "r"(tid));
    }
    if (__builtin_expect(tid < (12 - 2 * NCPA) * 32, 1)) {
        if (elect()) {
            const int w8 = (tid >> 5) * 8 + 16 * NCPA;
            const uint32_t b = bars + B_WQ * 8 + w8;
            mbar_init(b, 1);
            issue8(sb + WQ_OFF + w8 * WQ_PITCH, WQ_PITCH, gwq + (size_t)(96 * r + w8) * 8192 + 512 * c, 8192, 512, b, pol);
            mbar_expect(b, 4096);
        }
    }
    const int warp = __shfl_sync(0xFFFFFFFFu, tid >> 5, 0);
    const int nK = r < 4 ? 11 : 10;
    const int nO = r < 4 ? 5 : 6;
    const int u0 = r < 5 ? 5 * r : 26;
    const int g = lane >> 2, t = lane & 3;
    const size_t kvbase = ((size_t)c * SK + (SK - WIN) + 32 * r) * 256;
    constexpr int KV_STEP = CS * 8192;
    unsigned t_start;
    asm volatile("mov.u32 %0, %%globaltimer_lo;" : "=r"(t_start));
    if (warp >= PW0) {
        if (elect()) {
            const int p = warp - PW0;
            if (p == 1) asm volatile("prefetch.tensormap [%0];" ::"l"(&m2) : "memory");
#pragma unroll
            for (int i = 0; i < 40 / NPROD; i++) {
                const uint32_t b = bars + 8 * (B_K + NPROD * i + p);
                mbar_init(b, 1); mbar_expect(b, NPROD * i + p < 22 ? 8192 : 9216);
            }
            if (p == 0) { mbar_init(bars + 8 * B_WQDONE, 16); mbar_init(bars + 8 * B_KDONE, NMMA); mbar_init(bars + 8 * B_VDONE, 8); }
        }
    } else if (warp == 16) {
        if (lane < 24) sts64(sb + ZERO_S + lane * 8, 0u, 0u);
    } else if (warp == 17) {
        if (elect()) {
            mbar_init(bars + 8 * B_X1, 1); mbar_init(bars + 8 * B_X2, 1); mbar_init(bars + 8 * B_X3, 1); mbar_init(bars + 8 * B_X4, 1); mbar_init(bars + 8 * B_X4S, 1);
            mbar_expect(bars + 8 * B_X1, CS * 1024); mbar_expect(bars + 8 * B_X2, CS * (nO * 32 + 16));
            mbar_expect(bars + 8 * B_X3, CS * 384); mbar_expect(bars + 8 * B_X4, CS * 384); mbar_expect(bars + 8 * B_X4S, 18 * 16);
            mbar_init(bars + 8 * B_H1G, 1); mbar_expect(bars + 8 * B_H1G, CS * 96 + 4);
            mbar_init(bars + 8 * B_Q, 2); mbar_init(bars + 8 * B_O, 2);
            mbar_init(bars + 8 * B_INIT, 1);
            asm volatile("fence.mbarrier_init.release.cluster;" ::: "memory");
        }
    } else if (warp == EW0) {
        const uint4* px = reinterpret_cast<const uint4*>(gx);
        const uint4 xv0 = __ldg(px + lane), xv1 = __ldg(px + 32 + lane);
        const uint4 xv2 = lane < 8 ? __ldg(px + 64 + lane) : make_uint4(0, 0, 0, 0);
        const uint32_t w[12] = {xv0.x, xv0.y, xv0.z, xv0.w, xv1.x, xv1.y, xv1.z, xv1.w, xv2.x, xv2.y, xv2.z, xv2.w};
        float s = 0.f;
#pragma unroll
        for (int i = 0; i < 12; i++) s += bflo(w[i]) + bfhi(w[i]);
#pragma unroll
        for (int m = 16; m; m >>= 1) s += shx(s, m);
        const float mean = s * (1.0f / DM);
        float q = 0.f;
#pragma unroll
        for (int i = 0; i < 12; i++) {
            const float a = bflo(w[i]) - mean, b = bfhi(w[i]) - mean;
            if (i < 8 || lane < 8) q += a * a + b * b;
        }
#pragma unroll
        for (int m = 16; m; m >>= 1) q += shx(q, m);
        const float mb = bfr(mean), sd = bfr(sqrt_fast(bfr(bfr(q * (1.0f / DM)) + 1e-5f)));
        if (lane == 0) stsf(sb + XSC_S, fmaxf(sqrt_fast(q * (1.0f / DM)), fabsf(mean)));
#pragma unroll
        for (int ch = 0; ch < 3; ch++) {
            const int lc = lane + 32 * ch - 12 * r;
            if (lc >= 0 && lc < 12) {
#pragma unroll
                for (int i = 0; i < 4; i++) {
                    const float a = bflo(w[4 * ch + i]), b = bfhi(w[4 * ch + i]);
                    const int k = 8 * lc + 2 * i;
                    const uint32_t pk = pack2(__fdividef(bfr(a - mb), sd), __fdividef(bfr(b - mb), sd));
                    asm volatile("st.shared.b32 [%0], %1;" ::"r"(sb + XN_S + 2 * pos16(k)), "r"(pk) : "memory");
                }
            }
        }
    }
    unsigned arrived = 0;
    if (warp == EW0 + 2) {
        asm volatile("barrier.cluster.arrive.relaxed.aligned;" ::: "memory");
        asm volatile("bar.arrive 2, %0;" ::"n"(NTHREADS) : "memory");
#pragma unroll
        for (int k = 0; k < 2; k++) {
            if (lane < 24) __stcg(&scr->side[k][cta * 24 + lane], make_uint4(SENT, SENT, SENT, SENT));
            else if (c < 6) __stcg(reinterpret_cast<uint4*>(scr->acc[k]) + (r * 6 + c) * 8 + lane - 24, make_uint4(0, 0, 0, 0));
        }
        asm volatile("fence.acq_rel.gpu;" ::: "memory");
        __syncwarp();
        if (lane == 0) asm volatile("atom.relaxed.gpu.global.inc.u32 %0, [%1], %2;" : "=r"(arrived) : "l"(G_ARRIVE), "n"(NCTA * 65536 - 1) : "memory");
    } else {
        __syncwarp();
        asm volatile("barrier.cluster.arrive.relaxed.aligned;" ::: "memory");
        if (warp >= PW0) asm volatile("bar.arrive 2, %0;" ::"n"(NTHREADS) : "memory");
        else {
            if (warp < 16) {
#pragma unroll
                for (int i = 0; i < NCPA; i++)
                    asm volatile("st.shared.v4.b32 [%0], {%1,%2,%3,%4};" ::"r"(sb + WQ_OFF + (warp + 16 * i) * WQ_PITCH + lane * 16), "r"(wq_r[i].x), "r"(wq_r[i].y), "r"(wq_r[i].z), "r"(wq_r[i].w) : "memory");
            }
            asm volatile("bar.sync 2, %0;" ::"n"(NTHREADS) : "memory");
        }
    }

    if (warp >= PW0) {
        asm volatile("bar.sync 3, %0;" ::"n"(NPROD * 32) : "memory");
        const int sV = nK, sO = 2 * nK, s1 = sO + nO, s2 = s1 + 6, total = s2 + 6;
        const int tauK = r < 4 ? T_K / 11 : T_K / 10, tauV = r < 4 ? T_V / 11 : T_V / 10, tauO = r < 4 ? T_O / 5 : T_O / 6;
        for (int s = warp - PW0; s < total; s += NPROD) {
            const char* src; uint32_t dst, dp, sp, bytes; int bar, ebar = -1, when;
            if (s < sO) {
                const bool isv = s >= sV;
                const int j = s - (isv ? sV : 0);
                src = (isv ? gv : gk) + kvbase + (size_t)j * KV_STEP;
                dst = isv ? (j < 8 ? V_OFF + j * KV_STAGE : (j - 8) * KV_STAGE) : K_OFF + j * KV_STAGE;
                dp = KV_GRP; sp = 1024; bytes = 1024; bar = (isv ? B_V : B_K) + j;
                if (isv && j >= 8) ebar = B_WQDONE;
                when = isv ? T_K + j * tauV : j * tauK;
            } else if (s < s1) {
                const int j = s - sO;
                src = gwo + (size_t)(256 * c + 8 * (u0 + j)) * 1152; dst = WO_OFF + j * WR_STAGE;
                dp = WR_PITCH; sp = 1152; bytes = 1152; bar = B_WO + j; ebar = j < 2 ? B_WQDONE : B_KDONE;
                when = T_K + T_V + j * tauO;
            } else if (s < s2) {
                const int j = s - s1;
                src = gw1 + (size_t)(96 * r + 16 * j) * (FF * 2) + 576 * c; dst = W1_OFF + j * W1_STAGE;
                dp = W1_PITCH; sp = FF * 2; bytes = 576; bar = B_W1 + j; ebar = B_KDONE;
                when = T_K + T_V + T_O + j * TAU_1;
            } else {
                const int j = s - s2;
                src = nullptr; dst = W2_OFF + j * W2_STAGE;
                dp = 0; sp = 288 * c + 48 * j; bytes = 0; bar = B_W2 + j; ebar = B_VDONE;
                when = T_K + T_V + T_O + 6 * TAU_1 + (j < 2 ? j * TAU_2A : 2 * TAU_2A + (j - 2) * TAU_2B);
            }
            if (ebar >= 0) { mbar_wait(bars + 8 * ebar); asm volatile("fence.proxy.async.shared::cta;" ::: "memory"); }
            const int dep = s - (s < sO ? WIN_CAP : s < s1 ? CAP_O : s < s2 ? CAP_1 : CAP_2);
            if (dep >= 0) mbar_wait(bars + 8 * (dep < sV ? B_K + dep : dep < sO ? B_V + dep - sV : dep < s1 ? B_WO + dep - sO : B_W1 + dep - s1));
            const unsigned t_go = t_start + PACE_T0 + ((when * pace) >> 10);
            for (int it = 0; it < 100000; it++) {
                unsigned now; asm volatile("mov.u32 %0, %%globaltimer_lo;" : "=r"(now));
                if ((int)(now - t_go) >= 0) break;
            }
            if (elect()) {
                if (bytes == 0) tma3(sb + dst, &m2, 3 * r, sp, bars + 8 * bar, pol);
                const int nh = bytes == 576 ? 2 : bytes ? 1 : 0;
#pragma unroll 1
                for (int h = 0; h < nh; h++) issue8(sb + dst + 8 * h * dp, dp, src + (size_t)(8 * h) * sp, sp, bytes, bars + 8 * bar, pol);
            }
            __syncwarp();
        }
        asm volatile("barrier.cluster.wait.aligned;" ::: "memory");
    } else if (warp >= EW0) {
        const int e = warp - EW0, et = tid - EW0 * 32;
        asm volatile("barrier.cluster.wait.aligned;" ::: "memory");
        if (e == 2) {
            if (lane == 0) {
                const bool last = arrived % NCTA == NCTA - 1;
                for (unsigned it = 0;; it++) {
                    unsigned v;
                    asm volatile("ld.acquire.gpu.global.u32 %0, [%1];" : "=r"(v) : "l"(G_ARRIVE) : "memory");
                    if (last || v / NCTA != arrived / NCTA) break;
                    __nanosleep(400);
                    if (it > SPIN_LIMIT) __trap();
                }
                mbar_arrive(bars + 8 * B_INIT);
            }
            __syncwarp();
        }
        if (e < 2) {
            mbar_wait(bars + 8 * B_X1);
            float a0 = 0.f, a1 = 0.f, a2 = 0.f, a3 = 0.f;
#pragma unroll
            for (int s = 0; s < CS; s++) {
                const uint4 v = lds128(sb + X1R + s * 1024 + et * 16);
                a0 += __uint_as_float(v.x); a1 += __uint_as_float(v.y); a2 += __uint_as_float(v.z); a3 += __uint_as_float(v.w);
            }
            const int w = et >> 2;
            const uint32_t qa = sb + Q_S + ((w >> 3) * 4 + (et & 3)) * 80 + (w & 7) * 8, q0 = pack2(a0, a2), q1 = pack2(a1, a3);
            sts64(qa, q0, q1); sts64(qa + 640, q1, q0);
            __syncwarp();
            if (lane == 0) mbar_arrive(bars + 8 * B_Q);
            mbar_wait(bars + 8 * B_X2);
            if (et < 8 * nO) {
                const int head = (u0 + (et >> 3)) >> 4;
                float m[CS], l[CS], o[CS];
#pragma unroll
                for (int s = 0; s < CS; s++) {
                    const uint2 v = lds64(sb + X2S + s * 16 + head * 8);
                    m[s] = __uint_as_float(v.x); l[s] = __uint_as_float(v.y);
                    o[s] = ldsf(sb + X2R + (s * 48 + et) * 4);
                }
                float M = m[0];
#pragma unroll
                for (int s = 1; s < CS; s++) M = fmaxf(M, m[s]);
                float L = 0.f, acc = 0.f;
#pragma unroll
                for (int s = 0; s < CS; s++) { const float ws = ex2((m[s] - M) * LOG2E); L += ws * l[s]; acc += ws * o[s]; }
                sts16(sb + O_S + 2 * et, f2bf(__fdividef(acc, L)));
            }
            __syncwarp();
            if (lane == 0) mbar_arrive(bars + 8 * B_O);
        }
        {
            unsigned long long* pa = pin(scr->acc[0] + 96 * r + et);
            uint32_t* side = reinterpret_cast<uint32_t*>(scr->side[0]) + r * NCL * 96 + et;
            const float xres = __bfloat162float(__ldg(gx + 96 * r + et));
            const int lc = et;
            const uint32_t hdst = pin(sb + H_S + 2 * pos16(lc));
            if (e == 2) mbar_wait(bars + 8 * B_O);
            const Fix fx = make_fix(ldsf(sb + XSC_S));
            mbar_wait(bars + 8 * B_INIT);
            mbar_wait(bars + 8 * B_X3);
            float a[CS];
#pragma unroll
            for (int s = 0; s < CS; s++) a[s] = ldsf(sb + X3R + (s * 96 + et) * 4);
            unsigned long long tot = fix_add(pa, side + c * 96, ((a[0] + a[1]) + (a[2] + a[3])) + (a[4] + a[5]), fx);
            for (unsigned it = 0; __any_sync(0xFFFFFFFFu, (tot & 31) != NCL); it++) {
                tot = atom_add64(pa, 0);
                if (it > SPIN_LIMIT) __trap();
            }
            const float attn = fix_value(tot, side, fx);
            const float h = bfr(xres + bfr(attn));
            sts16(hdst, (uint16_t)(__float_as_uint(h) >> 16));
            __syncwarp();
            asm volatile("bar.arrive 4, %0;" ::"n"(NMMA * 32 + 96) : "memory");
            const float k0 = __shfl_sync(0xFFFFFFFFu, h, 0);
            float s = h - k0, q = s * s;
#pragma unroll
            for (int m = 16; m; m >>= 1) { s += shx(s, m); q += shx(q, m); }
            if (lane < CS) st_async4(mapa(sb + X4S + (r * 3 + e) * 16, lane), k0, s, q, 0.f, mapa(bars + 8 * B_X4S, lane));
        }
        {
            mbar_wait(bars + 8 * B_X4S);
            const float kc = ldsf(sb + X4S);
            const uint4 st = lds128(sb + X4S + (lane < 18 ? lane : 0) * 16);
            const float dk = __uint_as_float(st.x) - kc, gs = __uint_as_float(st.y);
            float s = lane < 18 ? gs + 32.0f * dk : 0.f;
            float q = lane < 18 ? __uint_as_float(st.z) + dk * (2.0f * gs + 32.0f * dk) : 0.f;
#pragma unroll
            for (int m = 16; m; m >>= 1) { s += shx(s, m); q += shx(q, m); }
            const float dm = s * (1.0f / DM);
            const float var = fmaxf(q * (1.0f / DM) - dm * dm, 0.f);
            const float mb = bfr(kc + dm), rsd = __fdividef(1.0f, bfr(sqrt_fast(bfr(bfr(var) + 1e-5f))));
            if (et == 0) st_async1(mapa(sb + XSC_S + 4, r), fmaxf(sqrt_fast(var), fabsf(kc + dm)), mapa(bars + 8 * B_H1G, r));
            const uint32_t ga = sb + H1G + (r * 24 + 8 * e + (g & 3) * 2 + (g >> 2)) * 4;
            mbar_wait(bars + 8 * B_X4);
            const int f = 16 * e + (lane >> 1);
            float s1 = 0.f, s2 = 0.f;
#pragma unroll
            for (int i = 0; i < 3; i++) {
                const uint2 v = lds64(sb + X4R + ((3 * (lane & 1) + i) * 48 + f) * 8);
                s1 += __uint_as_float(v.x); s2 += __uint_as_float(v.y);
            }
            float pre = s1 - mb * s2;
            pre = bfr((pre + shx(pre, 1)) * rsd);
            const float act = __fdividef(pre, 1.0f + ex2(-pre * LOG2E));
            const float nb = shx(act, 2);
            const float v = __uint_as_float((lane & 2) ? pack2(nb, act) : pack2(act, nb));
            st_async1(mapa(ga, t), v, mapa(bars + 8 * B_H1G, t));
            if (t < 2) st_async1(mapa(ga, t + 4), v, mapa(bars + 8 * B_H1G, t + 4));
        }
    } else {
        const int w = warp;
        const int cx = ((lane >> 3) ^ (lane >> 2)) & 1;
        const bool act = (t >> 1) == (g & 1);
        if (w < 16) {
            uint2 b[6];
#pragma unroll
            for (int ks = 0; ks < 6; ks++) b[ks] = lds64(sb + (act ? XN_S : ZERO_S) + (ks * 4 + t) * 8);
            float acc[2][4] = {};
            const uint32_t ab = sb + WQ_OFF + ((lane & 7) + 8 * (lane >> 4)) * WQ_PITCH + (2 * w + cx) * 16;
#pragma unroll
            for (int ks = 0; ks < 6; ks++) {
                if (ks >= NCPA) { mbar_wait(bars + 8 * (B_WQ + 2 * ks)); mbar_wait(bars + 8 * (B_WQ + 2 * ks + 1)); }
                uint32_t a[4]; ldsm4t(a, ab + ks * WQ_STAGE);
                mma16(acc[ks & 1], a, b[ks].x, b[ks].y);
            }
            const float c0 = (acc[0][0] + acc[1][0]) + (acc[0][3] + acc[1][3]), c2 = (acc[0][2] + acc[1][2]) + (acc[0][1] + acc[1][1]);
            asm volatile("barrier.cluster.wait.aligned;" ::: "memory");
            const uint32_t da = sb + X1R + r * 1024 + (w * 8 + g) * 8;
            st_async2(mapa(da, t), c0, c2, mapa(bars + 8 * B_X1, t));
            if (t < 2) st_async2(mapa(da, t + 4), c0, c2, mapa(bars + 8 * B_X1, t + 4));
            if (lane == 0) mbar_arrive(bars + 8 * B_WQDONE);
        } else {
            asm volatile("barrier.cluster.wait.aligned;" ::: "memory");
        }
        const int head = t & 1, half = t >> 1;
        float sc[2];
        {
            mbar_wait(bars + 8 * B_Q);
            uint32_t qb[16];
#pragma unroll
            for (int j = 0; j < 4; j++) {
                const uint4 v = lds128(sb + Q_S + (((g >> 1) & 1) * 8 + (g & 1) * 4 + t) * 80 + j * 16);
                qb[4 * j] = v.x; qb[4 * j + 1] = v.y; qb[4 * j + 2] = v.z; qb[4 * j + 3] = v.w;
            }
#pragma unroll
            for (int it = 0; it < 2; it++) {
                const int tau = w + NMMA * it;
                sc[it] = -INFINITY;
                if (tau < 2 * nK) {
                    mbar_wait(bars + 8 * (B_K + (tau >> 1)));
                    const uint32_t ab = sb + K_OFF + (tau >> 1) * KV_STAGE + (lane & 7) * KV_GRP + ((tau & 1) * 2 + ((lane >> 3) & 1)) * 256 + (((lane >> 4) ^ (lane >> 2)) & 1) * 16;
                    float acc[2][4] = {};
#pragma unroll
                    for (int ks = 0; ks < 8; ks++) {
                        uint32_t a[4]; ldsm4(a, ab + ks * 32);
                        mma16(acc[ks & 1], a, qb[2 * ks], qb[2 * ks + 1]);
                    }
                    const float x0 = half ? acc[0][2] + acc[1][2] : acc[0][0] + acc[1][0], x1 = half ? acc[0][3] + acc[1][3] : acc[0][1] + acc[1][1];
                    const float other = shx(head ? x0 : x1, 1);
                    const float raw = head == (g >> 2) ? (head ? x1 : x0) : other;
                    sc[it] = bfr(bfr(raw) * 0.08838834764831845f);
                }
            }
        }
        float M = fmaxf(sc[0], sc[1]);
#pragma unroll
        for (int m = 2; m <= 16; m <<= 1) M = fmaxf(M, shx(M, m));
        if (lane < 2) stsf(sb + WMAX + (2 * w + lane) * 4, M);
        if (lane == 0) mbar_arrive(bars + 8 * B_KDONE);
        bar_mma();
        M = ldsf(sb + WMAX + lane * 4);
        if (lane < 4) M = fmaxf(M, ldsf(sb + WMAX + (32 + lane) * 4));
#pragma unroll
        for (int m = 2; m <= 16; m <<= 1) M = fmaxf(M, shx(M, m));
        {
            float ls = 0.f;
#pragma unroll
            for (int it = 0; it < 2; it++) {
                const int tau = w + NMMA * it;
                if (tau < 2 * nK) {
                    const float pb = bfr(ex2((sc[it] - M) * LOG2E));
                    ls += pb;
                    sts16(sb + P_S + head * 704 + (tau * 16 + (g >> 1) * 4 + half * 2 + (g & 1)) * 2, (uint16_t)(__float_as_uint(pb) >> 16));
                }
            }
#pragma unroll
            for (int m = 2; m <= 16; m <<= 1) ls += shx(ls, m);
            if (lane < 2) stsf(sb + WSUM + (2 * w + lane) * 4, ls);
        }
        bar_mma();
        if (w == 8) {
            float L = ldsf(sb + WSUM + lane * 4);
            if (lane < 4) L += ldsf(sb + WSUM + (32 + lane) * 4);
#pragma unroll
            for (int m = 2; m <= 16; m <<= 1) L += shx(L, m);
            const float Mo = shx(M, 1), Lo = shx(L, 1);
            if (lane < CS) st_async4(mapa(sb + X2S + r * 16, lane), head ? Mo : M, head ? Lo : L, head ? M : Mo, head ? L : Lo, mapa(bars + 8 * B_X2, lane));
        }
        if (w < 8) {
            float acc[2][4] = {};
            const uint32_t ao = sb + (lane & 7) * KV_GRP + (lane >> 4) * 256 + (2 * w + cx) * 16;
            const uint32_t pb = sb + P_S + (g & 1) * 704 + t * 8;
            const uint32_t pm = (t >> 1) == ((g >> 1) & 1) ? 0xFFFFFFFFu : 0u;
#pragma unroll
            for (int j = 0; j < 11; j++) {
                if (j < nK) {
                    const uint2 b0 = lds64(pb + j * 64), b1 = lds64(pb + j * 64 + 32);
                    mbar_wait(bars + 8 * (B_V + j));
                    const uint32_t ab = ao + (j < 8 ? V_OFF + j * KV_STAGE : (j - 8) * KV_STAGE);
                    uint32_t a0[4], a1[4];
                    ldsm4t(a0, ab); ldsm4t(a1, ab + 512);
                    mma16(acc[0], a0, b0.x & pm, b0.y & pm);
                    mma16(acc[1], a1, b1.x & pm, b1.y & pm);
                    if (j == 6 && lane == 0) mbar_arrive(bars + 8 * B_VDONE);
                }
            }
            const float own = half ? acc[0][1] + acc[1][1] : acc[0][0] + acc[1][0], snd = half ? acc[0][3] + acc[1][3] : acc[0][2] + acc[1][2];
            const float val = own + shx(snd, 1);
            const int u = 16 * half + 2 * w + head;
            const int dest = u < 20 ? u / 5 : (u < 26 ? 4 : 5);
            const int ud = u - (dest < 5 ? 5 * dest : 26);
            st_async1(mapa(sb + X2R + (r * 48 + ud * 8 + g) * 4, dest), val, mapa(bars + 8 * B_X2, dest));
        }
        const int rd = w / 3, jd = w - 3 * rd;
        const uint32_t wro = pin(sb + (lane & 7) * WR_PITCH + (lane >> 4) * WR_STAGE + (4 * w + cx) * 16);
        {
            const uint32_t da = mapa(sb + X3R + (r * 96 + 32 * jd + 8 * t + g) * 4, rd), db = mapa(bars + 8 * B_X3, rd);
            mbar_wait(bars + 8 * B_O);
            uint32_t b[6];
#pragma unroll
            for (int u = 0; u < 6; u++) b[u] = lds32(sb + (act ? O_S : ZERO_S) + (8 * u + 2 * t) * 2);
            if (nO == 5) b[5] = 0;
            float accA[4] = {}, accB[4] = {};
#pragma unroll
            for (int u = 0; u < 6; u += 2) {
                mbar_wait(bars + 8 * (B_WO + u));
                uint32_t ad = wro + WO_OFF + u * WR_STAGE, a0[4], a1[4];
                if (u + 1 < nO) mbar_wait(bars + 8 * (B_WO + u + 1));
                else ad -= (lane >> 4) * WR_STAGE;
                ldsm4t(a0, ad); ldsm4t(a1, ad + 32);
                mma16(accA, a0, b[u], b[u + 1]);
                mma16(accB, a1, b[u], b[u + 1]);
            }
            st_async1(da, pick4(accA[0], accA[2], accB[0], accB[2], t) + pick4(accA[3], accA[1], accB[3], accB[1], t), db);
        }
        {
            uint32_t a[6][4];
            float cs[4] = {};
            const uint32_t ab = sb + W1_OFF + ((lane & 7) + 8 * (lane >> 4)) * W1_PITCH + (2 * w + cx) * 16;
            const uint32_t ones = act ? 0x3F803F80u : 0u;
#pragma unroll
            for (int ks = 0; ks < W1PRE; ks++) { mbar_wait(bars + 8 * (B_W1 + ks)); ldsm4t(a[ks], ab + ks * W1_STAGE); mma16(cs, a[ks], ones, ones); }
            const uint32_t hb = pin(sb + (act ? H_S : ZERO_S) + t * 8);
            const uint32_t da = pin(mapa(sb + X4R + (r * 48 + 16 * jd + 8 * (t & 1) + g) * 8, rd)), db = pin(mapa(bars + 8 * B_X4, rd));
            asm volatile("bar.sync 4, %0;" ::"n"(NMMA * 32 + 96) : "memory");
            float acc[2][4] = {};
            uint2 b[6];
#pragma unroll
            for (int ks = 0; ks < 6; ks++) b[ks] = lds64(hb + ks * 32);
#pragma unroll
            for (int ks = 0; ks < W1PRE; ks++) mma16(acc[ks & 1], a[ks], b[ks].x, b[ks].y);
#pragma unroll
            for (int ks = W1PRE; ks < 6; ks++) {
                mbar_wait(bars + 8 * (B_W1 + ks)); ldsm4t(a[ks], ab + ks * W1_STAGE);
                mma16(acc[ks & 1], a[ks], b[ks].x, b[ks].y); mma16(cs, a[ks], ones, ones);
            }
            const float s2 = (t & 1) ? cs[2] + cs[1] : cs[0] + cs[3];
            if (t < 2) {
                const float s1 = t ? (acc[0][2] + acc[1][2]) + (acc[0][1] + acc[1][1]) : (acc[0][0] + acc[1][0]) + (acc[0][3] + acc[1][3]);
                st_async2(da, s1, s2, db);
            }
            __syncwarp();
        }
        if (w < 6) {
            const int col = 16 * w + 8 * (t & 1) + g, row = (lane & 7) + 8 * (lane >> 4);
            const int lin = row * 192 + (w >> 1) * 64;
            const uint32_t ab = pin(sb + W2_OFF + lin + (((2 * (w & 1) + ((lane >> 3) & 1)) ^ ((lin >> 7) & 3)) * 16));
            constexpr int KS = 3072;
            unsigned long long* pa = pin(scr->acc[1] + 96 * r + col);
            uint32_t* side = reinterpret_cast<uint32_t*>(scr->side[1]) + r * NCL * 96 + col;
            uint16_t* pout = pin(reinterpret_cast<uint16_t*>(gout) + 96 * r + col);
            uint16_t hb16; asm volatile("ld.shared.u16 %0, [%1];" : "=h"(hb16) : "r"(sb + H_S + 2 * pos16(col)) : "memory");
            const float h = pinf(__uint_as_float((uint32_t)hb16 << 16));
            mbar_wait(bars + 8 * B_H1G);
            const Fix fh = make_fix(ldsf(sb + XSC_S + 4));
            const uint32_t tp = pin((uint32_t)t);
            float acc[2][3][4] = {};
            uint32_t a[2][3][4], b[2][3][2];
#pragma unroll
            for (int j = 0; j <= 6; j++) {
                if (j < 6) {
#pragma unroll
                    for (int i = 0; i < 3; i++) {
                        const uint2 v = lds64(sb + H1G + j * 96 + i * 32 + t * 8);
                        b[j & 1][i][0] = v.x; b[j & 1][i][1] = v.y;
                    }
                    mbar_wait(bars + 8 * (B_W2 + j));
#pragma unroll
                    for (int i = 0; i < 3; i++) ldsm4t(a[j & 1][i], ab + j * W2_STAGE + i * KS);
                }
                if (j > 0) {
#pragma unroll
                    for (int i = 0; i < 3; i++) mma16(acc[~j & 1][i], a[~j & 1][i], b[~j & 1][i][0], b[~j & 1][i][1]);
                }
            }
            if (tp < 2) {
                const float p0 = tp ? (acc[0][0][2] + acc[0][1][2]) + acc[0][2][2] : (acc[0][0][0] + acc[0][1][0]) + acc[0][2][0];
                const float part = tp ? (p0 + acc[1][0][2]) + (acc[1][1][2] + acc[1][2][2]) : (p0 + acc[1][0][0]) + (acc[1][1][0] + acc[1][2][0]);
                const unsigned long long tot = fix_add(pa, side + c * 96, part, fh);
                if ((tot & 31) == NCL) *pout = f2bf(h + bfr(fix_value(tot, side, fh)));
            }
        }
    }
}

struct FbScratch { float q[4096], o[4096], h[DM], a[FF]; };
__device__ FbScratch g_fb;
typedef __nv_bfloat16 bf;

template <int MODE>
__global__ void __launch_bounds__(64) fb_gemv(const bf* __restrict__ x, const bf* __restrict__ W, bf* __restrict__ out) {
    constexpr int K = MODE == 1 ? 4096 : MODE == 3 ? FF : DM, N = MODE == 0 ? 4096 : MODE == 2 ? FF : DM;
    __shared__ float in[K];
    for (int k = threadIdx.x; k < K; k += 64) in[k] = MODE == 0 ? __bfloat162float(x[k]) : MODE == 1 ? g_fb.o[k] : MODE == 2 ? g_fb.h[k] : g_fb.a[k];
    __syncthreads();
    if (MODE == 0 || MODE == 2) {
        float s = 0.f, q = 0.f;
        for (int k = 0; k < K; k++) s += in[k];
        const float mean = s / K;
        for (int k = 0; k < K; k++) q += (in[k] - mean) * (in[k] - mean);
        const float mb = bfr(mean), sd = bfr(sqrtf(bfr(bfr(q / K) + 1e-5f)));
        __syncthreads();
        for (int k = threadIdx.x; k < K; k += 64) in[k] = bfr(bfr(in[k] - mb) / sd);
        __syncthreads();
    }
    const int n = blockIdx.x * 64 + threadIdx.x;
    float acc = 0.f;
    for (int k = 0; k < K; k++) acc += in[k] * __bfloat162float(W[(size_t)k * N + n]);
    acc = bfr(acc);
    if (MODE == 0) g_fb.q[n] = acc;
    if (MODE == 1) g_fb.h[n] = bfr(__bfloat162float(x[n]) + acc);
    if (MODE == 2) g_fb.a[n] = bfr(acc / (1.0f + expf(-acc)));
    if (MODE == 3) out[n] = __float2bfloat16_rn(g_fb.h[n] + acc);
}
__global__ void __launch_bounds__(128) fb_attn(const bf* __restrict__ K, const bf* __restrict__ V) {
    __shared__ float s[WIN];
    const int hq = blockIdx.x;
    const size_t base = ((size_t)(hq >> 1) * SK + (SK - WIN)) * 128;
    for (int j = threadIdx.x; j < WIN; j += 128) {
        float a = 0.f;
        for (int d = 0; d < 128; d++) a += g_fb.q[hq * 128 + d] * __bfloat162float(K[base + (size_t)j * 128 + d]);
        s[j] = bfr(bfr(a) * 0.08838834764831845f);
    }
    __syncthreads();
    float m = -INFINITY, l = 0.f, acc = 0.f;
    for (int j = 0; j < WIN; j++) m = fmaxf(m, s[j]);
    for (int j = 0; j < WIN; j++) l += expf(s[j] - m);
    for (int j = 0; j < WIN; j++) acc += bfr(expf(s[j] - m) / l) * __bfloat162float(V[base + (size_t)j * 128 + threadIdx.x]);
    g_fb.o[hq * 128 + threadIdx.x] = bfr(acc);
}

}

typedef CUresult (*EncodeFn)(CUtensorMap*, CUtensorMapDataType, cuuint32_t, void*, const cuuint64_t*, const cuuint64_t*, const cuuint32_t*,
                             const cuuint32_t*, CUtensorMapInterleave, CUtensorMapSwizzle, CUtensorMapL2promotion, CUtensorMapFloatOOBfill);

extern "C" void kernel_launch(void* const* d_in, const int* in_sizes, int n_in, void* d_out, int out_size) {
    (void)in_sizes; (void)n_in; (void)out_size;
    static bool configured = false, fused_ok = false;
    static EncodeFn enc = nullptr;
    static Scratch* scr = nullptr;
    static int pace = 1024;
    if (!configured) {
        configured = true;
        cudaFuncSetAttribute(fused_decode_kernel, cudaFuncAttributeMaxDynamicSharedMemorySize, SMEM_BYTES);
        cudaGetSymbolAddress((void**)&scr, g_scratch);
        void* fn = nullptr;
        cudaDriverEntryPointQueryResult qr;
        if (cudaGetDriverEntryPoint("cuTensorMapEncodeTiled", &fn, cudaEnableDefault, &qr) == cudaSuccess) enc = (EncodeFn)fn;
        cudaLaunchConfig_t cfg = {};
        cfg.gridDim = dim3(CS, NCL); cfg.blockDim = dim3(NTHREADS); cfg.dynamicSmemBytes = SMEM_BYTES;
        cudaLaunchAttribute at;
        at.id = cudaLaunchAttributeClusterDimension; at.val.clusterDim.x = CS; at.val.clusterDim.y = 1; at.val.clusterDim.z = 1;
        cfg.attrs = &at; cfg.numAttrs = 1;
        int dev = 0, khz = 0, bits = 0;
        if (cudaGetDevice(&dev) == cudaSuccess && cudaDeviceGetAttribute(&khz, cudaDevAttrMemoryClockRate, dev) == cudaSuccess &&
            cudaDeviceGetAttribute(&bits, cudaDevAttrGlobalMemoryBusWidth, dev) == cudaSuccess && khz > 0 && bits > 0) {
            const double q = 1024.0 * (2619000.0 * 5120.0) / ((double)khz * bits);
            pace = q < 512.0 ? 512 : q > 2048.0 ? 2048 : (int)(q + 0.5);
        }
        int nclusters = 0;
        fused_ok = enc && scr && cudaOccupancyMaxActiveClusters(&nclusters, fused_decode_kernel, &cfg) == cudaSuccess && nclusters >= NCL;
        (void)cudaGetLastError();
    }
    CUtensorMap m2;
    const cuuint64_t dims[3] = {32, 18, FF}, strides[2] = {64, 1152};
    const cuuint32_t box[3] = {32, 3, 48}, es[3] = {1, 1, 1};
    if (fused_ok && enc(&m2, CU_TENSOR_MAP_DATA_TYPE_BFLOAT16, 3, d_in[7], dims, strides, box, es, CU_TENSOR_MAP_INTERLEAVE_NONE, CU_TENSOR_MAP_SWIZZLE_64B,
                        CU_TENSOR_MAP_L2_PROMOTION_L2_128B, CU_TENSOR_MAP_FLOAT_OOB_FILL_NONE) == CUDA_SUCCESS) {
        fused_decode_kernel<<<dim3(CS, NCL), NTHREADS, SMEM_BYTES>>>(
            (const bf*)d_in[0], (const char*)d_in[1], (const char*)d_in[2], (const char*)d_in[3],
            (const char*)d_in[4], (const char*)d_in[6], (bf*)d_out, scr, pace, m2);
    } else {
        const bf* x = (const bf*)d_in[0];
        fb_gemv<0><<<64, 64>>>(x, (const bf*)d_in[3], nullptr);
        fb_attn<<<32, 128>>>((const bf*)d_in[1], (const bf*)d_in[2]);
        fb_gemv<1><<<9, 64>>>(x, (const bf*)d_in[4], nullptr);
        fb_gemv<2><<<72, 64>>>(x, (const bf*)d_in[6], nullptr);
        fb_gemv<3><<<9, 64>>>(x, (const bf*)d_in[7], (bf*)d_out);
    }
}
```
